```python
import torch

def _softmax(x, axis=-1):
    return torch.softmax(x, dim=axis)
def _gelu(x):
    return torch.nn.functional.gelu(x, approximate="tanh")
def _silu(x):
    return torch.nn.functional.silu(x)
def _sigmoid(x):
    return torch.sigmoid(x)
def _layernorm(x, axis=-1, eps=1e-5):
    m = x.mean(dim=axis, keepdim=True)
    v = x.var(dim=axis, keepdim=True, unbiased=False)
    return (x - m) / torch.sqrt(v + eps)
def _scatter_add(tgt, idx, src, axis=0):
    return tgt.clone().index_add_(axis, idx, src)
def _segment_sum(src, seg, n):
    out = torch.zeros((n,) + src.shape[1:], dtype=src.dtype)
    return out.index_add_(0, seg, src)
def _pad(x, pw):
    flat = tuple(v for pair in reversed(pw) for v in pair)
    return torch.nn.functional.pad(x, flat)

kernel_name = 'standalone__deep_cross_wide_deep__recsys'

def setup_inputs():

    _w = (lambda a: (lambda t: t.to(torch.bfloat16) if t.is_floating_point() else t)(torch.as_tensor(a)))
    B, F, D = 16384, 100, 32
    V, Nd = min(1000, 100000), 13
    Din = F * D
    H = 4 * D
    return {
        "idx": _w((lambda lo, hi, *s: torch.randint(lo, hi, s))(0, V, B, F).to(torch.int64)),
        "table": _w((lambda *s: torch.randn(*s, dtype=torch.bfloat16) * 1.6)(V, D) * 0.05),
        "x_wide": _w((lambda *s: torch.randn(*s, dtype=torch.bfloat16) * 1.6)(B, Nd)),
        "w_wide": _w((lambda *s: torch.randn(*s, dtype=torch.bfloat16) * 1.6)(Nd) * 0.05),
        "b_wide": _w((lambda *s: torch.randn(*s, dtype=torch.bfloat16) * 1.6)(1) * 0.01),
        "W1": _w((lambda *s: torch.randn(*s, dtype=torch.bfloat16) * 1.6)(Din, H) * (2.0 / Din) ** 0.5),
        "b1": _w((lambda *s: torch.randn(*s, dtype=torch.bfloat16) * 1.6)(H) * 0.01),
        "W2": _w((lambda *s: torch.randn(*s, dtype=torch.bfloat16) * 1.6)(H) * (1.0 / H) ** 0.5),
        "b2": _w((lambda *s: torch.randn(*s, dtype=torch.bfloat16) * 1.6)(1) * 0.01),
    }

def reference(idx, table, x_wide, w_wide, b_wide, W1, b1, W2, b2):
    emb = table[idx]
    deep_in = emb.reshape(emb.shape[0], -1)
    h = deep_in @ W1 + b1
    h = h * (lambda x, dt: x.to(dt))(h > 0, h.dtype)
    deep_logit = h @ W2 + b2
    wide_logit = x_wide @ w_wide + b_wide
    return _sigmoid(wide_logit + deep_logit)
```

```cpp
#include <cuda_runtime.h>
#include <cuda_bf16.h>
#include <cuda.h>
#include <stdint.h>

#define NSTAGES 5
#define PF_MODE 1

namespace wd {

constexpr int kB = 16384, kF = 100, kD = 32, kH = 128, kV = 1000, kNd = 13;
constexpr int BM = 128;
constexpr int NCTA = kB / BM;
constexpr int FPS = 2;
constexpr int STAGE_BYTES = FPS * kD * kH * 2;
constexpr int NST = NSTAGES;
constexpr int NSTEP = kF / FPS;
constexpr int UN = 10;
constexpr int NOUT = NSTEP / UN;
constexpr int IDX_CH = 20;
constexpr int TBL_BYTES = kV * kD * 2;

constexpr int OFF_W = 0;
constexpr int OFF_TBL = OFF_W + NST * STAGE_BYTES;
constexpr int OFF_EPI = OFF_TBL + TBL_BYTES;
constexpr int OFF_BAR = OFF_EPI + 1040;
constexpr int BAR_FULL = OFF_BAR;
constexpr int BAR_EMPTY = BAR_FULL + 8 * NST;
constexpr int BAR_TBL = BAR_EMPTY + 8 * NST;
constexpr int BAR_EPI = BAR_TBL + 8;
constexpr int SMEM_BYTES = BAR_EPI + 8;
static_assert(SMEM_BYTES <= 232448, "smem");

constexpr int NTHREADS = 320;

#define TS(i)
#define TSC(i)
#define TSPARAM

__device__ __forceinline__ uint32_t smem_u32(const void* p) {
    return (uint32_t)__cvta_generic_to_shared(p);
}
__device__ __forceinline__ void mbar_init(uint32_t bar, uint32_t cnt) {
    asm volatile("mbarrier.init.shared::cta.b64 [%0], %1;" ::"r"(bar), "r"(cnt) : "memory");
}
__device__ __forceinline__ void mbar_expect_tx(uint32_t bar, uint32_t bytes) {
    asm volatile("mbarrier.arrive.expect_tx.shared::cta.b64 _, [%0], %1;" ::"r"(bar), "r"(bytes) : "memory");
}
__device__ __forceinline__ void mbar_arrive(uint32_t bar) {
    asm volatile("mbarrier.arrive.shared::cta.b64 _, [%0];" ::"r"(bar) : "memory");
}
__device__ __forceinline__ bool mbar_test(uint32_t bar, uint32_t parity) {
    uint32_t ok;
    asm volatile(
        "{\n\t.reg .pred p;\n\t"
        "mbarrier.test_wait.parity.shared::cta.b64 p, [%1], %2;\n\t"
        "selp.u32 %0, 1, 0, p;\n\t}"
        : "=r"(ok) : "r"(bar), "r"(parity) : "memory");
    return ok != 0;
}
__device__ __forceinline__ void mbar_wait(uint32_t bar, uint32_t parity) {
    asm volatile(
        "{\n\t.reg .pred p;\n\t.reg .u32 n;\n\t"
        "mov.u32 n, 0;\n\t"
        "W_LOOP:\n\t"
        "mbarrier.try_wait.parity.shared::cta.b64 p, [%0], %1;\n\t"
        "@p bra W_DONE;\n\t"
        "add.u32 n, n, 1;\n\t"
        "setp.lt.u32 p, n, 4194304;\n\t"
        "@p bra W_LOOP;\n\t"
        "trap;\n\t"
        "W_DONE:\n\t}"
        ::"r"(bar), "r"(parity) : "memory");
}
__device__ __forceinline__ uint4 lds128(uint32_t addr) {
    uint4 v;
    asm volatile("ld.shared.v4.u32 {%0,%1,%2,%3}, [%4];" : "=r"(v.x), "=r"(v.y), "=r"(v.z), "=r"(v.w) : "r"(addr));
    return v;
}
__device__ __forceinline__ uint4 tex128(cudaTextureObject_t t, int i) {
    uint4 v;
    asm volatile("tex.1d.v4.s32.s32 {%0,%1,%2,%3}, [%4, {%5}];"
                 : "=r"(v.x), "=r"(v.y), "=r"(v.z), "=r"(v.w) : "l"(t), "r"(i));
    return v;
}
__device__ __forceinline__ void l2_prefetch(const void* p, uint32_t bytes) {
    asm volatile("cp.async.bulk.prefetch.L2.global [%0], %1;" ::"l"(p), "r"(bytes) : "memory");
}

__device__ __forceinline__ void wgmma_fence() { asm volatile("wgmma.fence.sync.aligned;" ::: "memory"); }
__device__ __forceinline__ void wgmma_commit() { asm volatile("wgmma.commit_group.sync.aligned;" ::: "memory"); }
template <int N>
__device__ __forceinline__ void wgmma_wait() { asm volatile("wgmma.wait_group.sync.aligned %0;" ::"n"(N) : "memory"); }

__device__ __forceinline__ void wgmma_rs(float (&d)[64], uint32_t a0, uint32_t a1, uint32_t a2, uint32_t a3,
                                         uint32_t desc_lo) {
    asm volatile(
        "{\n\t.reg .b64 dsc;\n\t"
        "mov.b64 dsc, {%68, %69};\n\t"
        "wgmma.mma_async.sync.aligned.m64n128k16.f32.bf16.bf16 "
        "{%0,%1,%2,%3,%4,%5,%6,%7,%8,%9,%10,%11,%12,%13,%14,%15,"
        "%16,%17,%18,%19,%20,%21,%22,%23,%24,%25,%26,%27,%28,%29,%30,%31,"
        "%32,%33,%34,%35,%36,%37,%38,%39,%40,%41,%42,%43,%44,%45,%46,%47,"
        "%48,%49,%50,%51,%52,%53,%54,%55,%56,%57,%58,%59,%60,%61,%62,%63},"
        "{%64,%65,%66,%67}, dsc, 1, 1, 1, 1;\n\t}"
        : "+f"(d[0]), "+f"(d[1]), "+f"(d[2]), "+f"(d[3]), "+f"(d[4]), "+f"(d[5]), "+f"(d[6]), "+f"(d[7]),
          "+f"(d[8]), "+f"(d[9]), "+f"(d[10]), "+f"(d[11]), "+f"(d[12]), "+f"(d[13]), "+f"(d[14]), "+f"(d[15]),
          "+f"(d[16]), "+f"(d[17]), "+f"(d[18]), "+f"(d[19]), "+f"(d[20]), "+f"(d[21]), "+f"(d[22]), "+f"(d[23]),
          "+f"(d[24]), "+f"(d[25]), "+f"(d[26]), "+f"(d[27]), "+f"(d[28]), "+f"(d[29]), "+f"(d[30]), "+f"(d[31]),
          "+f"(d[32]), "+f"(d[33]), "+f"(d[34]), "+f"(d[35]), "+f"(d[36]), "+f"(d[37]), "+f"(d[38]), "+f"(d[39]),
          "+f"(d[40]), "+f"(d[41]), "+f"(d[42]), "+f"(d[43]), "+f"(d[44]), "+f"(d[45]), "+f"(d[46]), "+f"(d[47]),
          "+f"(d[48]), "+f"(d[49]), "+f"(d[50]), "+f"(d[51]), "+f"(d[52]), "+f"(d[53]), "+f"(d[54]), "+f"(d[55]),
          "+f"(d[56]), "+f"(d[57]), "+f"(d[58]), "+f"(d[59]), "+f"(d[60]), "+f"(d[61]), "+f"(d[62]), "+f"(d[63])
        : "r"(a0), "r"(a1), "r"(a2), "r"(a3), "r"(desc_lo), "n"(0x40000000 | (4096 >> 4)));
}

__device__ __forceinline__ float bf16r(float x) { return __bfloat162float(__float2bfloat16_rn(x)); }

struct Frag { uint4 x0, y0, x1, y1; };

__global__ void __launch_bounds__(NTHREADS, 1)
wide_deep_kernel(const int* __restrict__ idx, const __nv_bfloat16* __restrict__ table,
                 const __nv_bfloat16* __restrict__ W1, cudaTextureObject_t idx_tex, uint32_t zero,
                 const __nv_bfloat16* __restrict__ x_wide,
                 const __nv_bfloat16* __restrict__ w_wide, const __nv_bfloat16* __restrict__ b_wide,
                 const __nv_bfloat16* __restrict__ b1, const __nv_bfloat16* __restrict__ W2,
                 const __nv_bfloat16* __restrict__ b2, __nv_bfloat16* __restrict__ out,
                 const __grid_constant__ CUtensorMap tmW, const __grid_constant__ CUtensorMap tmI TSPARAM) {
    extern __shared__ __align__(1024) uint8_t smem_raw[];
    const uint32_t sb = smem_u32(smem_raw);
    const int tid = threadIdx.x;
    const int warp = __shfl_sync(0xffffffffu, tid >> 5, 0);
    const int lane = tid & 31;
    const int row0 = blockIdx.x * BM;

    if (warp == 8) {
        if (lane == 0) {
            TS(0); TSC(8);
            if (PF_MODE & 1) {
                l2_prefetch((const uint8_t*)W1 + blockIdx.x * 640, 640);
                if (blockIdx.x < 125) l2_prefetch((const uint8_t*)table + blockIdx.x * 512, 512);
            }
            asm volatile("prefetch.tensormap [%0];" ::"l"(&tmW) : "memory");
            mbar_init(sb + BAR_TBL, 1);
            for (int s = 0; s < NST; s++) mbar_init(sb + BAR_FULL + 8 * s, 1);
            asm volatile("fence.mbarrier_init.release.cluster;" ::: "memory");
            auto load_w = [&](int step, int slot) {
                const uint32_t bar = sb + BAR_FULL + 8 * slot;
                mbar_expect_tx(bar, STAGE_BYTES);
                asm volatile(
                    "cp.async.bulk.tensor.5d.shared::cluster.global.mbarrier::complete_tx::bytes "
                    "[%0], [%1, {0, 0, %3, 0, 0}], [%2];"
                    ::"r"(sb + OFF_W + slot * STAGE_BYTES), "l"(&tmW), "r"(bar), "r"(step * (4 * FPS)) : "memory");
            };
            auto pf_idx = [&](int c) {
                asm volatile("cp.async.bulk.prefetch.tensor.2d.L2.global [%0, {%1, %2}];"
                             ::"l"(&tmI), "r"(c * IDX_CH), "r"(row0) : "memory");
            };
            if (PF_MODE & 2) load_w(0, 0);
            mbar_expect_tx(sb + BAR_TBL, TBL_BYTES);
            asm volatile(
                "cp.async.bulk.shared::cluster.global.mbarrier::complete_tx::bytes [%0], [%1], %2, [%3];"
                ::"r"(sb + OFF_TBL), "l"(table), "r"(TBL_BYTES), "r"(sb + BAR_TBL) : "memory");
            if (!(PF_MODE & 2)) load_w(0, 0);
            asm volatile("prefetch.tensormap [%0];" ::"l"(&tmI) : "memory");
            for (int s = 0; s < NST; s++) mbar_init(sb + BAR_EMPTY + 8 * s, 2);
            mbar_init(sb + BAR_EPI, 32);
            asm volatile("fence.mbarrier_init.release.cluster;" ::: "memory");
            load_w(1, 1);
            pf_idx(0);
            for (int s = 2; s < NST; s++) load_w(s, s);
            TS(1);
        }
        __syncthreads();
        if (lane == 0) {
            int slot = 0;
            uint32_t ph = 0;
            int nextc = 1;
#pragma unroll 1
            for (int step = NST; step < NSTEP; step++) {
                mbar_wait(sb + BAR_EMPTY + 8 * slot, ph);
                mbar_expect_tx(sb + BAR_FULL + 8 * slot, STAGE_BYTES);
                asm volatile(
                    "cp.async.bulk.tensor.5d.shared::cluster.global.mbarrier::complete_tx::bytes "
                    "[%0], [%1, {0, 0, %3, 0, 0}], [%2];"
                    ::"r"(sb + OFF_W + slot * STAGE_BYTES), "l"(&tmW), "r"(sb + BAR_FULL + 8 * slot),
                      "r"(step * (4 * FPS)) : "memory");
                if (++slot == NST) { slot = 0; ph ^= 1; }
                if (nextc < kF / IDX_CH && step == NST + (nextc - 1) * 6) {
                    asm volatile("cp.async.bulk.prefetch.tensor.2d.L2.global [%0, {%1, %2}];"
                                 ::"l"(&tmI), "r"(nextc * IDX_CH), "r"(row0) : "memory");
                    nextc++;
                }
            }
        }
    } else if (warp == 9) {
        __syncthreads();
        mbar_wait(sb + BAR_EMPTY, 0);
        uint32_t* epi = (uint32_t*)(smem_raw + OFF_EPI);
#pragma unroll
        for (int h = 0; h < 2; h++) {
            const int w = lane + 32 * h;
            epi[(w & 3) * 16 + (w >> 2)] = __ldg((const uint32_t*)b1 + w);
            epi[64 + (w & 3) * 16 + (w >> 2)] = __ldg((const uint32_t*)W2 + w);
        }
        const float bw = __bfloat162float(b_wide[0]);
#pragma unroll
        for (int r = 0; r < 4; r++) {
            const __nv_bfloat16* x = x_wide + (size_t)(row0 + lane + 32 * r) * kNd;
            float s = 0.f;
#pragma unroll
            for (int j = 0; j < kNd; j++) s = fmaf(__bfloat162float(x[j]), __bfloat162float(w_wide[j]), s);
            ((float*)epi)[128 + lane + 32 * r] = bf16r(bf16r(s) + bw);
        }
        if (lane == 0) ((float*)epi)[256] = __bfloat162float(b2[0]);
        mbar_arrive(sb + BAR_EPI);
    } else {
        const int g = lane >> 2, q = lane & 3;
        const int r0 = warp * 16 + g;
        const uint4* ip = (const uint4*)(idx + (size_t)(row0 + r0) * kF);
        uint4 i0 = __ldg(ip), i1 = __ldg(ip + 8 * kF / 4);
        uint4 n0 = __ldg(ip + 1), n1 = __ldg(ip + 8 * kF / 4 + 1);
        int tcoord = (row0 + r0) * (kF / 4) + 2;

        float acc[64];
#pragma unroll
        for (int i = 0; i < 64; i++) acc[i] = 0.f;

        const uint32_t tbase = sb + OFF_TBL + q * 16;
        auto gaddr = [&](uint32_t v) -> uint32_t { return tbase + v * 64; };
        auto opq = [&](uint4 t) {
            uint4 r;
            asm volatile("xor.b32 %0, %1, %2;" : "=r"(r.x) : "r"(t.x), "r"(zero));
            asm volatile("xor.b32 %0, %1, %2;" : "=r"(r.y) : "r"(t.y), "r"(zero));
            asm volatile("xor.b32 %0, %1, %2;" : "=r"(r.z) : "r"(t.z), "r"(zero));
            asm volatile("xor.b32 %0, %1, %2;" : "=r"(r.w) : "r"(t.w), "r"(zero));
            return r;
        };
        const bool signaller = (tid & 127) == 0;
        const uint32_t desc0 = (((sb + OFF_W) & 0x3FFFF) >> 4) | ((8192 >> 4) << 16);

        __syncthreads();
        mbar_wait(sb + BAR_TBL, 0);
        Frag A[2];
        A[0].x0 = lds128(gaddr(i0.x)); A[0].y0 = lds128(gaddr(i1.x));
        A[0].x1 = lds128(gaddr(i0.y)); A[0].y1 = lds128(gaddr(i1.y));
        bool ok = false;

#pragma unroll 1
        for (int o = 0; o < NOUT; o++) {
#pragma unroll
            for (int u = 0; u < UN; u++) {
                const int slot = u % NST;
                const Frag& a = A[u & 1];
                if (!ok) mbar_wait(sb + BAR_FULL + 8 * slot, NST == UN ? (o & 1) : (u / NST));
                Frag t;
                uint32_t g0, g1, g2, g3;
                if ((u & 1) == 0) {
                    g0 = gaddr(i0.z); g1 = gaddr(i1.z); g2 = gaddr(i0.w); g3 = gaddr(i1.w);
                } else {
                    i0 = n0; i1 = n1;
                    g0 = gaddr(i0.x); g1 = gaddr(i1.x); g2 = gaddr(i0.y); g3 = gaddr(i1.y);
                    if (u < 7 || o + 1 < NOUT) {
                        n0 = tex128(idx_tex, tcoord);
                        n1 = tex128(idx_tex, tcoord + 8 * (kF / 4));
                        tcoord++;
                    }
                }
                const uint32_t d = desc0 + slot * (STAGE_BYTES >> 4);
                wgmma_fence();
                t.x0 = lds128(g0);
                wgmma_rs(acc, a.x0.x, a.y0.x, a.x0.z, a.y0.z, d);
                __syncwarp();
                t.y0 = lds128(g1);
                wgmma_rs(acc, a.x0.y, a.y0.y, a.x0.w, a.y0.w, d + 128);
                __syncwarp();
                t.x1 = lds128(g2);
                wgmma_rs(acc, a.x1.x, a.y1.x, a.x1.z, a.y1.z, d + 64);
                __syncwarp();
                t.y1 = lds128(g3);
                wgmma_rs(acc, a.x1.y, a.y1.y, a.x1.w, a.y1.w, d + 192);
                wgmma_commit();
                wgmma_wait<1>();
                ok = mbar_test(sb + BAR_FULL + 8 * ((u + 1) % NST),
                               NST == UN ? ((o + (u + 1) / UN) & 1) : (((u + 1) / NST) & 1));
                {
                    const int pslot = (u + NST - 1) % NST;
                    const bool rel = (u == 0) ? (o > 0) : (u <= UN - NST ? true : (o + 1 < NOUT));
                    if (rel && signaller) mbar_arrive(sb + BAR_EMPTY + 8 * pslot);
                }
                Frag& an = A[(u + 1) & 1];
                an.x0 = opq(t.x0); an.y0 = opq(t.y0); an.x1 = opq(t.x1); an.y1 = opq(t.y1);
            }
        }
        mbar_wait(sb + BAR_EPI, 0);
        uint32_t b1p[16], w2p[16];
#pragma unroll
        for (int j = 0; j < 4; j++) {
            const uint4 v = lds128(sb + OFF_EPI + q * 64 + j * 16);
            const uint4 w = lds128(sb + OFF_EPI + 256 + q * 64 + j * 16);
            b1p[4 * j] = v.x; b1p[4 * j + 1] = v.y; b1p[4 * j + 2] = v.z; b1p[4 * j + 3] = v.w;
            w2p[4 * j] = w.x; w2p[4 * j + 1] = w.y; w2p[4 * j + 2] = w.z; w2p[4 * j + 3] = w.w;
        }
        const float wide = ((const float*)(smem_raw + OFF_EPI + 512))[r0 + 8 * (q & 1)];
        const float b2f = *(const float*)(smem_raw + OFF_EPI + 1024);
        wgmma_wait<0>();
#pragma unroll
        for (int i = 0; i < 64; i++) asm volatile("" : "+f"(acc[i])::"memory");
        if (tid == 0) { TS(6); TSC(10); }
        float c0[4] = {0.f, 0.f, 0.f, 0.f}, c1[4] = {0.f, 0.f, 0.f, 0.f};
        const uint32_t one2 = 0x3f803f80u;
#pragma unroll
        for (int s = 0; s < 8; s++) {
            uint32_t a[4];
#pragma unroll
            for (int i = 0; i < 4; i++) {
                uint32_t p;
                asm("cvt.rn.bf16x2.f32 %0, %1, %2;" : "=r"(p) : "f"(acc[8 * s + 2 * i + 1]), "f"(acc[8 * s + 2 * i]));
                asm("fma.rn.relu.bf16x2 %0, %1, %2, %3;" : "=r"(a[i]) : "r"(p), "r"(one2), "r"(b1p[2 * s + (i >> 1)]));
            }
            float* c = (s & 1) ? c1 : c0;
            asm volatile(
                "mma.sync.aligned.m16n8k16.row.col.f32.bf16.bf16.f32 {%0,%1,%2,%3}, {%4,%5,%6,%7}, {%8,%9}, {%0,%1,%2,%3};"
                : "+f"(c[0]), "+f"(c[1]), "+f"(c[2]), "+f"(c[3])
                : "r"(a[0]), "r"(a[1]), "r"(a[2]), "r"(a[3]), "r"(w2p[2 * s]), "r"(w2p[2 * s + 1]));
        }
        const float deep = (q & 1) ? (c0[2] + c1[2]) : (c0[0] + c1[0]);
        const float z = bf16r(wide + bf16r(bf16r(deep) + b2f));
        const float p = __fdividef(1.f, 1.f + __expf(-z));
        if (q < 2) out[row0 + r0 + 8 * q] = __float2bfloat16_rn(p);
        if (tid == 0) { TS(7); TSC(11); }
    }
}

typedef CUresult (*EncodeTiledFn)(CUtensorMap*, CUtensorMapDataType, cuuint32_t, void*, const cuuint64_t*,
                                  const cuuint64_t*, const cuuint32_t*, const cuuint32_t*, CUtensorMapInterleave,
                                  CUtensorMapSwizzle, CUtensorMapL2promotion, CUtensorMapFloatOOBfill);

}

extern "C" void kernel_launch(void* const* d_in, const int* in_sizes, int n_in, void* d_out, int out_size) {
    using namespace wd;
    (void)in_sizes; (void)n_in; (void)out_size;
    static EncodeTiledFn encode = nullptr;
    static cudaTextureObject_t idx_tex = 0;
    static const void* idx_tex_ptr = nullptr;
    if (!encode) {
        void* fn = nullptr;
        cudaDriverEntryPointQueryResult qr;
        cudaGetDriverEntryPoint("cuTensorMapEncodeTiled", &fn, cudaEnableDefault, &qr);
        encode = (EncodeTiledFn)fn;
        cudaFuncSetAttribute(wide_deep_kernel, cudaFuncAttributeMaxDynamicSharedMemorySize, SMEM_BYTES);
    }
    if (idx_tex_ptr != d_in[0]) {
        cudaResourceDesc rd = {};
        rd.resType = cudaResourceTypeLinear;
        rd.res.linear.devPtr = d_in[0];
        rd.res.linear.desc = cudaCreateChannelDesc(32, 32, 32, 32, cudaChannelFormatKindSigned);
        rd.res.linear.sizeInBytes = (size_t)kB * kF * 4;
        cudaTextureDesc td = {};
        td.readMode = cudaReadModeElementType;
        cudaCreateTextureObject(&idx_tex, &rd, &td, nullptr);
        idx_tex_ptr = d_in[0];
    }

    CUtensorMap tmW, tmI;
    {
        cuuint64_t dims[5] = {64, 2, 4 * (cuuint64_t)kF, 4, 2};
        cuuint64_t strides[4] = {256, 8 * 256, 2 * 256, 128};
        cuuint32_t box[5] = {64, 2, 4 * FPS, 4, 2};
        cuuint32_t es[5] = {1, 1, 1, 1, 1};
        encode(&tmW, CU_TENSOR_MAP_DATA_TYPE_BFLOAT16, 5, d_in[5], dims, strides, box, es,
               CU_TENSOR_MAP_INTERLEAVE_NONE, CU_TENSOR_MAP_SWIZZLE_128B, CU_TENSOR_MAP_L2_PROMOTION_L2_256B,
               CU_TENSOR_MAP_FLOAT_OOB_FILL_NONE);
    }
    {
        cuuint64_t dims[2] = {(cuuint64_t)kF, (cuuint64_t)kB};
        cuuint64_t strides[1] = {(cuuint64_t)kF * 4};
        cuuint32_t box[2] = {IDX_CH, BM};
        cuuint32_t es[2] = {1, 1};
        encode(&tmI, CU_TENSOR_MAP_DATA_TYPE_INT32, 2, d_in[0], dims, strides, box, es,
               CU_TENSOR_MAP_INTERLEAVE_NONE, CU_TENSOR_MAP_SWIZZLE_NONE, CU_TENSOR_MAP_L2_PROMOTION_NONE,
               CU_TENSOR_MAP_FLOAT_OOB_FILL_NONE);
    }
    wide_deep_kernel<<<NCTA, NTHREADS, SMEM_BYTES, cudaStreamPerThread>>>(
        (const int*)d_in[0], (const __nv_bfloat16*)d_in[1], (const __nv_bfloat16*)d_in[5], idx_tex, 0u,
        (const __nv_bfloat16*)d_in[2], (const __nv_bfloat16*)d_in[3], (const __nv_bfloat16*)d_in[4],
        (const __nv_bfloat16*)d_in[6], (const __nv_bfloat16*)d_in[7], (const __nv_bfloat16*)d_in[8],
        (__nv_bfloat16*)d_out, tmW, tmI
    );
}
```

```cpp
#include <cuda_runtime.h>
#include <cuda_bf16.h>
#include <cuda.h>
#include <stdint.h>

#define ABIT 0

namespace wd {

constexpr int kB = 16384, kF = 100, kD = 32, kH = 128, kV = 1000, kNd = 13;
constexpr int BM = 128;
constexpr int NCTA = kB / BM;
constexpr int FPS = 2;
constexpr int STAGE_BYTES = FPS * kD * kH * 2;
constexpr int NST = 5;
constexpr int NSTEP = kF / FPS;
constexpr int UN = 2 * NST;
constexpr int NOUT = NSTEP / UN;
constexpr int IDX_F0 = 12;
constexpr int IDX_CH = 24;
constexpr int PITCH4 = kF / 2;
constexpr int TBL_BYTES = kV * kD * 2;
constexpr int X_BYTES = 2 * BM * kNd * 2;

constexpr int OFF_W = 0;
constexpr int OFF_TBL = OFF_W + NST * STAGE_BYTES;
constexpr int OFF_W2 = OFF_TBL + TBL_BYTES;
constexpr int OFF_B1 = OFF_W2 + 256;
constexpr int OFF_WIDE = OFF_B1 + 256;
constexpr int OFF_X = OFF_WIDE + 8 * BM;
constexpr int BAR_FULL = OFF_X + X_BYTES;
constexpr int BAR_EMPTY = BAR_FULL + 8 * NST;
constexpr int BAR_TBL = BAR_EMPTY + 8 * NST;
constexpr int BAR_B1 = BAR_TBL + 8;
constexpr int BAR_X = BAR_B1 + 8;
constexpr int BAR_EPI = BAR_X + 8;
constexpr int SMEM_BYTES = BAR_EPI + 8;
static_assert(SMEM_BYTES <= 232448, "smem");
static_assert(OFF_TBL % 64 == 0 && OFF_B1 % 16 == 0 && OFF_X % 16 == 0 && BAR_FULL % 8 == 0, "align");

constexpr int NTHREADS = 320;

__device__ __forceinline__ uint32_t smem_u32(const void* p) { return (uint32_t)__cvta_generic_to_shared(p); }
__device__ __forceinline__ void mbar_init(uint32_t bar, uint32_t cnt) {
    asm volatile("mbarrier.init.shared::cta.b64 [%0], %1;" ::"r"(bar), "r"(cnt) : "memory");
}
__device__ __forceinline__ void mbar_init_fence() {
    asm volatile("fence.mbarrier_init.release.cluster;" ::: "memory");
}
__device__ __forceinline__ void mbar_expect_tx(uint32_t bar, uint32_t bytes) {
    asm volatile("mbarrier.arrive.expect_tx.shared::cta.b64 _, [%0], %1;" ::"r"(bar), "r"(bytes) : "memory");
}
__device__ __forceinline__ void mbar_arrive(uint32_t bar) {
    asm volatile("mbarrier.arrive.shared::cta.b64 _, [%0];" ::"r"(bar) : "memory");
}
__device__ __forceinline__ uint32_t mbar_test(uint32_t bar, uint32_t parity) {
    uint32_t ok;
    asm volatile(
        "{\n\t.reg .pred p;\n\t"
        "mbarrier.test_wait.parity.shared::cta.b64 p, [%1], %2;\n\t"
        "selp.u32 %0, 1, 0, p;\n\t}"
        : "=r"(ok) : "r"(bar), "r"(parity) : "memory");
    return ok;
}
__device__ __forceinline__ void mbar_wait(uint32_t bar, uint32_t parity) {
    asm volatile(
        "{\n\t.reg .pred p;\n\t.reg .u32 n;\n\t"
        "mov.u32 n, 0;\n\t"
        "W_LOOP:\n\t"
        "mbarrier.try_wait.parity.shared::cta.b64 p, [%0], %1;\n\t"
        "@p bra W_DONE;\n\t"
        "add.u32 n, n, 1;\n\t"
        "setp.lt.u32 p, n, 4194304;\n\t"
        "@p bra W_LOOP;\n\t"
        "trap;\n\t"
        "W_DONE:\n\t}"
        ::"r"(bar), "r"(parity) : "memory");
}
__device__ __forceinline__ void bulk_load(uint32_t dst, const void* src, uint32_t bytes, uint32_t bar) {
    mbar_expect_tx(bar, bytes);
    asm volatile("cp.async.bulk.shared::cluster.global.mbarrier::complete_tx::bytes [%0], [%1], %2, [%3];"
                 ::"r"(dst), "l"(src), "r"(bytes), "r"(bar) : "memory");
}
__device__ __forceinline__ void prefetch_line(const void* p) {
    asm volatile("prefetch.global.L2 [%0];" ::"l"(p) : "memory");
}
__device__ __forceinline__ uint4 lds128(uint32_t addr) {
    uint4 v;
    asm volatile("ld.shared.v4.u32 {%0,%1,%2,%3}, [%4];" : "=r"(v.x), "=r"(v.y), "=r"(v.z), "=r"(v.w) : "r"(addr));
    return v;
}
__device__ __forceinline__ uint4 ldg128(const uint4* p) {
    uint4 v;
    asm volatile("ld.global.v4.u32 {%0,%1,%2,%3}, [%4];"
                 : "=r"(v.x), "=r"(v.y), "=r"(v.z), "=r"(v.w) : "l"(p) : "memory");
    return v;
}
__device__ __forceinline__ uint4 tex128(cudaTextureObject_t t, int i) {
    uint4 v;
    asm volatile("tex.1d.v4.s32.s32 {%0,%1,%2,%3}, [%4, {%5}];"
                 : "=r"(v.x), "=r"(v.y), "=r"(v.z), "=r"(v.w) : "l"(t), "r"(i));
    return v;
}
__device__ __forceinline__ bool elect() {
    uint32_t p;
    asm volatile("{\n\t.reg .pred P;\n\telect.sync _|P, 0xffffffff;\n\tselp.u32 %0, 1, 0, P;\n\t}" : "=r"(p));
    return p != 0;
}
__device__ __forceinline__ uint4 copy4(uint4 t, uint32_t z) {
    uint4 r;
    asm volatile("xor.b32 %0, %1, %2;" : "=r"(r.x) : "r"(t.x), "r"(z));
    asm volatile("xor.b32 %0, %1, %2;" : "=r"(r.y) : "r"(t.y), "r"(z));
    asm volatile("xor.b32 %0, %1, %2;" : "=r"(r.z) : "r"(t.z), "r"(z));
    asm volatile("xor.b32 %0, %1, %2;" : "=r"(r.w) : "r"(t.w), "r"(z));
    return r;
}
__device__ __forceinline__ uint32_t pin(uint32_t v, int lane) { return __shfl_sync(0xffffffffu, v, lane); }

__device__ __forceinline__ void wgmma_fence() { asm volatile("wgmma.fence.sync.aligned;" ::: "memory"); }
__device__ __forceinline__ void wgmma_commit() { asm volatile("wgmma.commit_group.sync.aligned;" ::: "memory"); }
template <int N>
__device__ __forceinline__ void wgmma_wait() { asm volatile("wgmma.wait_group.sync.aligned %0;" ::"n"(N) : "memory"); }

__device__ __forceinline__ void wgmma_rs(float (&d)[64], uint32_t a0, uint32_t a1, uint32_t a2, uint32_t a3,
                                         uint32_t desc_lo) {
    asm volatile(
        "{\n\t.reg .b64 dsc;\n\t"
        "mov.b64 dsc, {%68, %69};\n\t"
        "wgmma.mma_async.sync.aligned.m64n128k16.f32.bf16.bf16 "
        "{%0,%1,%2,%3,%4,%5,%6,%7,%8,%9,%10,%11,%12,%13,%14,%15,"
        "%16,%17,%18,%19,%20,%21,%22,%23,%24,%25,%26,%27,%28,%29,%30,%31,"
        "%32,%33,%34,%35,%36,%37,%38,%39,%40,%41,%42,%43,%44,%45,%46,%47,"
        "%48,%49,%50,%51,%52,%53,%54,%55,%56,%57,%58,%59,%60,%61,%62,%63},"
        "{%64,%65,%66,%67}, dsc, 1, 1, 1, 1;\n\t}"
        : "+f"(d[0]), "+f"(d[1]), "+f"(d[2]), "+f"(d[3]), "+f"(d[4]), "+f"(d[5]), "+f"(d[6]), "+f"(d[7]),
          "+f"(d[8]), "+f"(d[9]), "+f"(d[10]), "+f"(d[11]), "+f"(d[12]), "+f"(d[13]), "+f"(d[14]), "+f"(d[15]),
          "+f"(d[16]), "+f"(d[17]), "+f"(d[18]), "+f"(d[19]), "+f"(d[20]), "+f"(d[21]), "+f"(d[22]), "+f"(d[23]),
          "+f"(d[24]), "+f"(d[25]), "+f"(d[26]), "+f"(d[27]), "+f"(d[28]), "+f"(d[29]), "+f"(d[30]), "+f"(d[31]),
          "+f"(d[32]), "+f"(d[33]), "+f"(d[34]), "+f"(d[35]), "+f"(d[36]), "+f"(d[37]), "+f"(d[38]), "+f"(d[39]),
          "+f"(d[40]), "+f"(d[41]), "+f"(d[42]), "+f"(d[43]), "+f"(d[44]), "+f"(d[45]), "+f"(d[46]), "+f"(d[47]),
          "+f"(d[48]), "+f"(d[49]), "+f"(d[50]), "+f"(d[51]), "+f"(d[52]), "+f"(d[53]), "+f"(d[54]), "+f"(d[55]),
          "+f"(d[56]), "+f"(d[57]), "+f"(d[58]), "+f"(d[59]), "+f"(d[60]), "+f"(d[61]), "+f"(d[62]), "+f"(d[63])
        : "r"(a0), "r"(a1), "r"(a2), "r"(a3), "r"(desc_lo), "n"(0x40000000 | (4096 >> 4)));
}

__device__ __forceinline__ float bf16r(float x) {
    uint32_t p;
    asm("cvt.rn.bf16x2.f32 %0, %1, %2;" : "=r"(p) : "f"(x), "f"(0.f));
    return __uint_as_float(p);
}

template <int N> struct IC { static constexpr int value = N; };
struct Frag { uint4 x0, y0, x1, y1; };

__global__ void __launch_bounds__(NTHREADS, 1)
wide_deep_kernel(const int* __restrict__ idx, const __nv_bfloat16* __restrict__ table,
                 const __nv_bfloat16* __restrict__ W1, cudaTextureObject_t idx_tex, uint32_t zero,
                 const __nv_bfloat16* __restrict__ b1, const __nv_bfloat16* __restrict__ x_wide,
                 const __nv_bfloat16* __restrict__ w_wide, const __nv_bfloat16* __restrict__ b_wide,
                 const __nv_bfloat16* __restrict__ W2, const __nv_bfloat16* __restrict__ b2,
                 __nv_bfloat16* __restrict__ out,
                 const __grid_constant__ CUtensorMap tmW, const __grid_constant__ CUtensorMap tmI) {
    extern __shared__ __align__(1024) uint8_t smem_raw[];
    const uint32_t sb = smem_u32(smem_raw);
    const int tid = threadIdx.x;
    const int lane = tid & 31;

    if (tid >= 288) {
        const int c = blockIdx.x & 31;
        if (lane < 16) prefetch_line((const uint8_t*)table + min(c * 16 + lane, 499) * 128);
        if (lane < 8) prefetch_line((const uint8_t*)W1 + (c * 4 + (lane >> 1) + (lane & 1) * ((NSTEP - 2) * 128)) * 128);
    }
    const int warp = __shfl_sync(0xffffffffu, tid >> 5, 0);

    const int asc = (blockIdx.x >> ABIT) & 1;
    const int pair = ((blockIdx.x >> (ABIT + 1)) << ABIT) | (blockIdx.x & ((1 << ABIT) - 1));
    const int prow0 = pair * BM;

    if (warp == 8) {
        auto load_w = [&](int step, int slot) {
            const int fp = asc ? step : (NSTEP - 2) - step + 2 * (step & 1);
            const uint32_t bar = sb + BAR_FULL + 8 * slot;
            mbar_expect_tx(bar, STAGE_BYTES);
            asm volatile(
                "cp.async.bulk.tensor.5d.shared::cluster.global.mbarrier::complete_tx::bytes "
                "[%0], [%1, {0, 0, %3, 0, 0}], [%2];"
                ::"r"(sb + OFF_W + slot * STAGE_BYTES), "l"(&tmW), "r"(bar), "r"(fp * (4 * FPS)) : "memory");
        };
        auto prefetch_idx = [&](int c) {
            const int f = IDX_F0 + c * IDX_CH;
            asm volatile("cp.async.bulk.prefetch.tensor.2d.L2.global [%0, {%1, %2}];"
                         ::"l"(&tmI), "r"(asc ? kF + f : kF - f - IDX_CH), "r"(prow0) : "memory");
        };
        if (elect()) {
            asm volatile("prefetch.tensormap [%0];" ::"l"(&tmW) : "memory");
            mbar_init(sb + BAR_TBL, 1);
            mbar_init(sb + BAR_FULL, 1);
            mbar_init(sb + BAR_B1, 1);
            mbar_init_fence();
            bulk_load(sb + OFF_B1, b1, 256, sb + BAR_B1);
            load_w(0, 0);
            bulk_load(sb + OFF_TBL, table, TBL_BYTES, sb + BAR_TBL);
            asm volatile("prefetch.tensormap [%0];" ::"l"(&tmI) : "memory");
            for (int s = 1; s < NST; s++) mbar_init(sb + BAR_FULL + 8 * s, 1);
            for (int s = 0; s < NST; s++) mbar_init(sb + BAR_EMPTY + 8 * s, 2);
            mbar_init(sb + BAR_X, 1);
            mbar_init(sb + BAR_EPI, 32);
            mbar_init_fence();
        }
        __syncthreads();
        if (elect()) {
            mbar_wait(sb + BAR_FULL, 0);
            load_w(1, 1);
            mbar_wait(sb + BAR_TBL, 0);
            for (int s = 2; s < NST; s++) load_w(s, s);
            prefetch_idx(0);
            constexpr int MID = (NSTEP - 2 * NST) * STAGE_BYTES / NCTA;
            asm volatile("cp.async.bulk.prefetch.L2.global [%0], %1;"
                         ::"l"((const uint8_t*)W1 + NST * STAGE_BYTES + blockIdx.x * MID), "n"(MID) : "memory");
            bulk_load(sb + OFF_X, (const uint8_t*)x_wide + pair * X_BYTES, X_BYTES, sb + BAR_X);
            int slot = 0, nextc = 1;
            uint32_t ph = 0;
#pragma unroll 1
            for (int step = NST; step < NSTEP; step++) {
                mbar_wait(sb + BAR_EMPTY + 8 * slot, ph);
                load_w(step, slot);
                if (++slot == NST) { slot = 0; ph ^= 1; }
                if (IDX_F0 + nextc * IDX_CH < kF && step == NST + nextc * 6) prefetch_idx(nextc++);
            }
        }
    } else if (warp == 9) {
        __syncthreads();
        if (lane < 2 * NST) {
            const int i = blockIdx.x * NST + (lane >> 1);
            prefetch_line((const uint8_t*)W1 + ((lane & 1) ? NSTEP * 128 - 1 - i : i) * 128);
        }
        {
            const int tc = (prow0 + lane) * PITCH4 + (kF / 4 - 1) + (asc ? 2 : -1);
            uint32_t x = 0;
#pragma unroll
            for (int r = 0; r < 4; r++) x |= tex128(idx_tex, tc + 32 * r * PITCH4).x;
            asm volatile("" ::"r"(x));
            if ((x & zero) != 0) __trap();
        }
        mbar_wait(sb + BAR_X, 0);
#pragma unroll
        for (int h = 0; h < 2; h++) {
            const int w = lane + 32 * h;
            ((uint32_t*)(smem_raw + OFF_W2))[(w & 48) + (w & 3) * 4 + ((w >> 2) & 3)] = __ldg((const uint32_t*)W2 + w);
        }
        const float wl = (lane >= asc && lane < kNd + asc) ? __bfloat162float(w_wide[lane - asc]) : 0.f;
        const float bw = __bfloat162float(b_wide[0]);
        const float b2v = __bfloat162float(b2[0]);
        float wt[14];
#pragma unroll
        for (int j = 0; j < 14; j++) wt[j] = __shfl_sync(0xffffffffu, wl, j);
#pragma unroll
        for (int r = 0; r < 4; r++) {
            const uint32_t* x = (const uint32_t*)(smem_raw + OFF_X) + (lane + 32 * r) * kNd + 6 * asc;
            float s = 0.f;
#pragma unroll
            for (int j = 0; j < 7; j++) {
                uint32_t v = x[j];
                if (j == 0 && asc) v &= 0xffff0000u;
                if (j == 6 && !asc) v &= 0x0000ffffu;
                s = fmaf(__uint_as_float(v << 16), wt[2 * j], s);
                s = fmaf(__uint_as_float(v & 0xffff0000u), wt[2 * j + 1], s);
            }
            ((float2*)(smem_raw + OFF_WIDE))[lane + 32 * r] = make_float2(bf16r(bf16r(s) + bw), b2v);
        }
        mbar_arrive(sb + BAR_EPI);
    } else {
        const int q = lane & 3;
        const int r0 = warp * 16 + (lane >> 2);
        const int tstep = asc ? 1 : -1;
        int tcoord = (prow0 + r0) * PITCH4 + (kF / 4 - 1) + asc;
        const uint4 f0 = ldg128((const uint4*)idx + tcoord), f1 = ldg128((const uint4*)idx + tcoord + 8 * PITCH4);
        tcoord += tstep;
        __syncthreads();

        float acc[64];
        mbar_wait(sb + BAR_B1, 0);
#pragma unroll
        for (int n = 0; n < 16; n++) {
            uint32_t v;
            asm volatile("ld.shared.u32 %0, [%1];" : "=r"(v) : "r"(sb + OFF_B1 + 16 * n + 4 * q) : "memory");
            acc[4 * n] = acc[4 * n + 2] = __uint_as_float(v << 16);
            acc[4 * n + 1] = acc[4 * n + 3] = __uint_as_float(v & 0xffff0000u);
        }
#pragma unroll
        for (int i = 0; i < 64; i++) asm volatile("" : "+f"(acc[i])::"memory");

        const uint64_t outp = (uint64_t)(out + 2 * (prow0 + r0 + 8 * (q & 1)) + asc);
        const uint32_t out_lo = pin((uint32_t)outp, lane), out_hi = pin((uint32_t)(outp >> 32), lane);
        const uint32_t wide_addr = pin(sb + OFF_WIDE + (r0 + 8 * (q & 1)) * 8, lane);
        const uint32_t tbase = pin(sb + OFF_TBL + q * 16, lane);
        auto gaddr = [&](uint32_t v) -> uint32_t { return tbase + v * 64; };
        const bool signaller = (tid & 127) == 0;
        const uint32_t desc0 = (((sb + OFF_W) & 0x3FFFF) >> 4) | ((8192 >> 4) << 16);

        mbar_wait(sb + BAR_FULL, 0);
        uint32_t ga[8] = {gaddr(f0.x), gaddr(f1.x), gaddr(f0.y), gaddr(f1.y),
                          gaddr(f0.z), gaddr(f1.z), gaddr(f0.w), gaddr(f1.w)};
#pragma unroll
        for (int i = 0; i < 8; i++) ga[i] = pin(ga[i], lane);
        mbar_wait(sb + BAR_TBL, 0);

        Frag A[2];
        uint4 i0 = f0, i1 = f1, n0, n1;
        bool ok;
        {
            Frag t;
            Frag& a = A[0];
            const uint4 x0 = lds128(ga[0]), y0 = lds128(ga[1]);
            __syncwarp();
            const uint4 x1 = lds128(ga[2]), y1 = lds128(ga[3]);
            __syncwarp();
            a.x0 = copy4(x0, zero); a.y0 = copy4(y0, zero);
            wgmma_fence();
            wgmma_rs(acc, a.x0.x, a.y0.x, a.x0.z, a.y0.z, desc0);
            __syncwarp();
            t.x0 = lds128(ga[4]);
            wgmma_rs(acc, a.x0.y, a.y0.y, a.x0.w, a.y0.w, desc0 + 128);
            wgmma_commit();
            wgmma_wait<1>();
            const uint32_t z1 = zero & mbar_test(sb + BAR_FULL, 0);
            t.y0 = lds128(ga[5]);
            n0 = tex128(idx_tex, tcoord);
            n1 = tex128(idx_tex, tcoord + 8 * PITCH4);
            tcoord += tstep;
            a.x1 = copy4(x1, z1); a.y1 = copy4(y1, z1);
            wgmma_fence();
            wgmma_rs(acc, a.x1.x, a.y1.x, a.x1.z, a.y1.z, desc0 + 64);
            __syncwarp();
            t.x1 = lds128(ga[6]);
            t.y1 = lds128(ga[7]);
            wgmma_rs(acc, a.x1.y, a.y1.y, a.x1.w, a.y1.w, desc0 + 192);
            wgmma_commit();
            wgmma_wait<1>();
            const uint32_t okv = mbar_test(sb + BAR_FULL + 8, 0);
            ok = okv != 0;
            const uint32_t z2 = zero & okv;
            A[1].x0 = copy4(t.x0, z2); A[1].y0 = copy4(t.y0, z2); A[1].x1 = copy4(t.x1, z2); A[1].y1 = copy4(t.y1, z2);
        }
        auto stage = [&](auto uc, int o) {
            constexpr int u = decltype(uc)::value;
            constexpr int slot = u % NST;
            const Frag& a = A[u & 1];
            if (u == UN - 3 && o + 1 == NOUT) mbar_wait(sb + BAR_EPI, 0);
            if (!ok) mbar_wait(sb + BAR_FULL + 8 * slot, u / NST);
            uint32_t g0, g1, g2, g3;
            if ((u & 1) == 0) {
                g0 = gaddr(i0.z); g1 = gaddr(i1.z); g2 = gaddr(i0.w); g3 = gaddr(i1.w);
            } else {
                i0 = n0; i1 = n1;
                g0 = gaddr(i0.x); g1 = gaddr(i1.x); g2 = gaddr(i0.y); g3 = gaddr(i1.y);
                if (u < UN - 3 || o + 1 < NOUT) {
                    n0 = tex128(idx_tex, tcoord);
                    n1 = tex128(idx_tex, tcoord + 8 * PITCH4);
                    tcoord += tstep;
                } else if (u == UN - 3) {
                    n0.x = kV; n1.x = kV + 1; n0.y = kV + 2; n1.y = kV + 3;
                }
            }
            const uint32_t d = desc0 + slot * (STAGE_BYTES >> 4);
            Frag t;
            wgmma_fence();
            t.x0 = lds128(g0);
            wgmma_rs(acc, a.x0.x, a.y0.x, a.x0.z, a.y0.z, d);
            __syncwarp();
            t.y0 = lds128(g1);
            wgmma_rs(acc, a.x0.y, a.y0.y, a.x0.w, a.y0.w, d + 128);
            __syncwarp();
            t.x1 = lds128(g2);
            wgmma_rs(acc, a.x1.x, a.y1.x, a.x1.z, a.y1.z, d + 64);
            __syncwarp();
            t.y1 = lds128(g3);
            wgmma_rs(acc, a.x1.y, a.y1.y, a.x1.w, a.y1.w, d + 192);
            wgmma_commit();
            wgmma_wait<1>();
            ok = mbar_test(sb + BAR_FULL + 8 * ((u + 1) % NST), ((u + 1) / NST) & 1) != 0;
            if ((u <= UN - NST || o + 1 < NOUT) && signaller) mbar_arrive(sb + BAR_EMPTY + 8 * ((u + NST - 1) % NST));
            Frag& an = A[(u + 1) & 1];
            an.x0 = copy4(t.x0, zero); an.y0 = copy4(t.y0, zero); an.x1 = copy4(t.x1, zero); an.y1 = copy4(t.y1, zero);
        };
#pragma unroll 1
        for (int o = 0;;) {
            stage(IC<1>{}, o); stage(IC<2>{}, o); stage(IC<3>{}, o);
            stage(IC<4>{}, o); stage(IC<5>{}, o); stage(IC<6>{}, o);
            stage(IC<7>{}, o); stage(IC<8>{}, o); stage(IC<9>{}, o);
            if (++o == NOUT) break;
            stage(IC<0>{}, o);
        }

        const uint32_t w2[16] = {A[0].x0.x, A[0].x0.y, A[0].x0.z, A[0].x0.w, A[0].y0.x, A[0].y0.y, A[0].y0.z, A[0].y0.w,
                                 A[0].x1.x, A[0].x1.y, A[0].x1.z, A[0].x1.w, A[0].y1.x, A[0].y1.y, A[0].y1.z, A[0].y1.w};
        float wide, b2f;
        asm volatile("ld.shared.v2.f32 {%0,%1}, [%2];" : "=f"(wide), "=f"(b2f) : "r"(wide_addr));
        wgmma_wait<0>();
#pragma unroll
        for (int i = 0; i < 64; i++) asm volatile("" : "+f"(acc[i])::"memory");
        float cc[4][4] = {};
#pragma unroll
        for (int s = 0; s < 8; s++) {
            uint32_t h[4];
#pragma unroll
            for (int i = 0; i < 4; i++)
                asm("cvt.rn.relu.bf16x2.f32 %0, %1, %2;" : "=r"(h[i]) : "f"(acc[8 * s + 2 * i + 1]), "f"(acc[8 * s + 2 * i]));
            float* c = cc[s & 3];
            asm volatile(
                "mma.sync.aligned.m16n8k16.row.col.f32.bf16.bf16.f32 {%0,%1,%2,%3}, {%4,%5,%6,%7}, {%8,%9}, {%0,%1,%2,%3};"
                : "+f"(c[0]), "+f"(c[1]), "+f"(c[2]), "+f"(c[3])
                : "r"(h[0]), "r"(h[1]), "r"(h[2]), "r"(h[3]), "r"(w2[2 * s]), "r"(w2[2 * s + 1]));
        }
        const bool hi = (tbase & 16) != 0;
        const float deep = hi ? (cc[0][2] + cc[1][2]) + (cc[2][2] + cc[3][2])
                              : (cc[0][0] + cc[1][0]) + (cc[2][0] + cc[3][0]);
        const float z = bf16r(wide + bf16r(bf16r(deep) + b2f));
        float e, p;
        asm("ex2.approx.ftz.f32 %0, %1;" : "=f"(e) : "f"(z * -1.4426950408889634f));
        asm("rcp.approx.ftz.f32 %0, %1;" : "=f"(p) : "f"(1.f + e));
        if (!(tbase & 32))
            asm volatile("st.global.b16 [%0], %1;" ::"l"(((uint64_t)out_hi << 32) | out_lo),
                         "h"(__bfloat16_as_ushort(__float2bfloat16_rn(p))) : "memory");
    }
}

typedef CUresult (*EncodeTiledFn)(CUtensorMap*, CUtensorMapDataType, cuuint32_t, void*, const cuuint64_t*,
                                  const cuuint64_t*, const cuuint32_t*, const cuuint32_t*, CUtensorMapInterleave,
                                  CUtensorMapSwizzle, CUtensorMapL2promotion, CUtensorMapFloatOOBfill);

}

extern "C" void kernel_launch(void* const* d_in, const int* in_sizes, int n_in, void* d_out, int out_size) {
    using namespace wd;
    (void)in_sizes; (void)n_in; (void)out_size;
    static EncodeTiledFn encode = nullptr;
    static cudaTextureObject_t idx_tex = 0;
    static const void* idx_tex_ptr = nullptr;
    if (!encode) {
        void* fn = nullptr;
        cudaDriverEntryPointQueryResult qr;
        cudaGetDriverEntryPoint("cuTensorMapEncodeTiled", &fn, cudaEnableDefault, &qr);
        encode = (EncodeTiledFn)fn;
        cudaFuncSetAttribute(wide_deep_kernel, cudaFuncAttributeMaxDynamicSharedMemorySize, SMEM_BYTES);
    }
    if (idx_tex_ptr != d_in[0]) {
        cudaResourceDesc rd = {};
        rd.resType = cudaResourceTypeLinear;
        rd.res.linear.devPtr = d_in[0];
        rd.res.linear.desc = cudaCreateChannelDesc(32, 32, 32, 32, cudaChannelFormatKindSigned);
        rd.res.linear.sizeInBytes = (size_t)kB * kF * 4;
        cudaTextureDesc td = {};
        td.readMode = cudaReadModeElementType;
        cudaCreateTextureObject(&idx_tex, &rd, &td, nullptr);
        idx_tex_ptr = d_in[0];
    }

    CUtensorMap tmW, tmI;
    {
        cuuint64_t dims[5] = {64, 2, 4 * (cuuint64_t)kF, 4, 2};
        cuuint64_t strides[4] = {256, 8 * 256, 2 * 256, 128};
        cuuint32_t box[5] = {64, 2, 4 * FPS, 4, 2};
        cuuint32_t es[5] = {1, 1, 1, 1, 1};
        encode(&tmW, CU_TENSOR_MAP_DATA_TYPE_BFLOAT16, 5, d_in[5], dims, strides, box, es,
               CU_TENSOR_MAP_INTERLEAVE_NONE, CU_TENSOR_MAP_SWIZZLE_128B, CU_TENSOR_MAP_L2_PROMOTION_L2_256B,
               CU_TENSOR_MAP_FLOAT_OOB_FILL_NONE);
    }
    {
        cuuint64_t dims[2] = {2 * (cuuint64_t)kF, (cuuint64_t)kB / 2};
        cuuint64_t strides[1] = {(cuuint64_t)kF * 8};
        cuuint32_t box[2] = {IDX_CH, BM};
        cuuint32_t es[2] = {1, 1};
        encode(&tmI, CU_TENSOR_MAP_DATA_TYPE_INT32, 2, d_in[0], dims, strides, box, es,
               CU_TENSOR_MAP_INTERLEAVE_NONE, CU_TENSOR_MAP_SWIZZLE_NONE, CU_TENSOR_MAP_L2_PROMOTION_NONE,
               CU_TENSOR_MAP_FLOAT_OOB_FILL_NONE);
    }
    wide_deep_kernel<<<NCTA, NTHREADS, SMEM_BYTES, cudaStreamPerThread>>>(
        (const int*)d_in[0], (const __nv_bfloat16*)d_in[1], (const __nv_bfloat16*)d_in[5], idx_tex, 0u,
        (const __nv_bfloat16*)d_in[6], (const __nv_bfloat16*)d_in[2], (const __nv_bfloat16*)d_in[3],
        (const __nv_bfloat16*)d_in[4], (const __nv_bfloat16*)d_in[7], (const __nv_bfloat16*)d_in[8],
        (__nv_bfloat16*)d_out, tmW, tmI);
}
```

```cpp
#include <cuda_runtime.h>
#include <cuda_bf16.h>
#include <cuda.h>
#include <stdint.h>

namespace wd {

constexpr int kB = 16384, kF = 100, kD = 32, kH = 128, kV = 1000, kNd = 13;
constexpr int BM = 128;
constexpr int NCTA = kB / BM;
constexpr int FPS = 2;
constexpr int STAGE_BYTES = FPS * kD * kH * 2;
constexpr int NST = 5;
constexpr int NSTEP = kF / FPS;
constexpr int UN = 2 * NST;
constexpr int NOUT = NSTEP / UN;
constexpr int IDX_F0 = 12;
constexpr int IDX_CH = 24;
constexpr int PITCH4 = kF / 2;
constexpr int TBL_BYTES = kV * kD * 2;
constexpr int X_BYTES = 2 * BM * kNd * 2;

constexpr int OFF_W = 0;
constexpr int OFF_TBL = OFF_W + NST * STAGE_BYTES;
constexpr int OFF_W2 = OFF_TBL + TBL_BYTES;
constexpr int OFF_B1 = OFF_W2 + 256;
constexpr int OFF_WIDE = OFF_B1 + 256;
constexpr int OFF_X = OFF_WIDE + 8 * BM;
constexpr int BAR_FULL = OFF_X + X_BYTES;
constexpr int BAR_EMPTY = BAR_FULL + 8 * NST;
constexpr int BAR_TBL = BAR_EMPTY + 8 * NST;
constexpr int BAR_B1 = BAR_TBL + 8;
constexpr int BAR_X = BAR_B1 + 8;
constexpr int BAR_EPI = BAR_X + 8;
constexpr int SMEM_BYTES = BAR_EPI + 8;
static_assert(SMEM_BYTES <= 232448, "smem");
static_assert(OFF_TBL % 64 == 0 && OFF_B1 % 16 == 0 && OFF_X % 16 == 0 && BAR_FULL % 8 == 0, "align");

constexpr int NTHREADS = 320;

__device__ __forceinline__ uint32_t smem_u32(const void* p) { return (uint32_t)__cvta_generic_to_shared(p); }
__device__ __forceinline__ void mbar_init(uint32_t bar, uint32_t cnt) {
    asm volatile("mbarrier.init.shared::cta.b64 [%0], %1;" ::"r"(bar), "r"(cnt) : "memory");
}
__device__ __forceinline__ void mbar_init_fence() {
    asm volatile("fence.mbarrier_init.release.cluster;" ::: "memory");
}
__device__ __forceinline__ void mbar_expect_tx(uint32_t bar, uint32_t bytes) {
    asm volatile("mbarrier.arrive.expect_tx.shared::cta.b64 _, [%0], %1;" ::"r"(bar), "r"(bytes) : "memory");
}
__device__ __forceinline__ void mbar_arrive(uint32_t bar) {
    asm volatile("mbarrier.arrive.shared::cta.b64 _, [%0];" ::"r"(bar) : "memory");
}
__device__ __forceinline__ uint32_t mbar_test(uint32_t bar, uint32_t parity) {
    uint32_t ok;
    asm volatile(
        "{\n\t.reg .pred p;\n\t"
        "mbarrier.test_wait.parity.shared::cta.b64 p, [%1], %2;\n\t"
        "selp.u32 %0, 1, 0, p;\n\t}"
        : "=r"(ok) : "r"(bar), "r"(parity) : "memory");
    return ok;
}
__device__ __forceinline__ void mbar_wait(uint32_t bar, uint32_t parity) {
    asm volatile(
        "{\n\t.reg .pred p;\n\t.reg .u32 n;\n\t"
        "mov.u32 n, 0;\n\t"
        "W_LOOP:\n\t"
        "mbarrier.try_wait.parity.shared::cta.b64 p, [%0], %1;\n\t"
        "@p bra W_DONE;\n\t"
        "add.u32 n, n, 1;\n\t"
        "setp.lt.u32 p, n, 4194304;\n\t"
        "@p bra W_LOOP;\n\t"
        "trap;\n\t"
        "W_DONE:\n\t}"
        ::"r"(bar), "r"(parity) : "memory");
}
__device__ __forceinline__ void bulk_load(uint32_t dst, const void* src, uint32_t bytes, uint32_t bar) {
    mbar_expect_tx(bar, bytes);
    asm volatile("cp.async.bulk.shared::cluster.global.mbarrier::complete_tx::bytes [%0], [%1], %2, [%3];"
                 ::"r"(dst), "l"(src), "r"(bytes), "r"(bar) : "memory");
}
__device__ __forceinline__ void prefetch_line(const void* p) {
    asm volatile("prefetch.global.L2 [%0];" ::"l"(p) : "memory");
}
__device__ __forceinline__ uint4 lds128(uint32_t addr) {
    uint4 v;
    asm volatile("ld.shared.v4.u32 {%0,%1,%2,%3}, [%4];" : "=r"(v.x), "=r"(v.y), "=r"(v.z), "=r"(v.w) : "r"(addr));
    return v;
}
__device__ __forceinline__ uint4 ldg128(const uint4* p) {
    uint4 v;
    asm volatile("ld.global.v4.u32 {%0,%1,%2,%3}, [%4];"
                 : "=r"(v.x), "=r"(v.y), "=r"(v.z), "=r"(v.w) : "l"(p) : "memory");
    return v;
}
__device__ __forceinline__ uint4 tex128(cudaTextureObject_t t, int i) {
    uint4 v;
    asm volatile("tex.1d.v4.s32.s32 {%0,%1,%2,%3}, [%4, {%5}];"
                 : "=r"(v.x), "=r"(v.y), "=r"(v.z), "=r"(v.w) : "l"(t), "r"(i));
    return v;
}
__device__ __forceinline__ bool elect() {
    uint32_t p;
    asm volatile("{\n\t.reg .pred P;\n\telect.sync _|P, 0xffffffff;\n\tselp.u32 %0, 1, 0, P;\n\t}" : "=r"(p));
    return p != 0;
}
__device__ __forceinline__ uint4 copy4(uint4 t, uint32_t z) {
    uint4 r;
    asm volatile("xor.b32 %0, %1, %2;" : "=r"(r.x) : "r"(t.x), "r"(z));
    asm volatile("xor.b32 %0, %1, %2;" : "=r"(r.y) : "r"(t.y), "r"(z));
    asm volatile("xor.b32 %0, %1, %2;" : "=r"(r.z) : "r"(t.z), "r"(z));
    asm volatile("xor.b32 %0, %1, %2;" : "=r"(r.w) : "r"(t.w), "r"(z));
    return r;
}
__device__ __forceinline__ uint32_t pin(uint32_t v, int lane) { return __shfl_sync(0xffffffffu, v, lane); }

__device__ __forceinline__ void wgmma_fence() { asm volatile("wgmma.fence.sync.aligned;" ::: "memory"); }
__device__ __forceinline__ void wgmma_commit() { asm volatile("wgmma.commit_group.sync.aligned;" ::: "memory"); }
template <int N>
__device__ __forceinline__ void wgmma_wait() { asm volatile("wgmma.wait_group.sync.aligned %0;" ::"n"(N) : "memory"); }

__device__ __forceinline__ void wgmma_rs(float (&d)[64], uint32_t a0, uint32_t a1, uint32_t a2, uint32_t a3,
                                         uint32_t desc_lo) {
    asm volatile(
        "{\n\t.reg .b64 dsc;\n\t"
        "mov.b64 dsc, {%68, %69};\n\t"
        "wgmma.mma_async.sync.aligned.m64n128k16.f32.bf16.bf16 "
        "{%0,%1,%2,%3,%4,%5,%6,%7,%8,%9,%10,%11,%12,%13,%14,%15,"
        "%16,%17,%18,%19,%20,%21,%22,%23,%24,%25,%26,%27,%28,%29,%30,%31,"
        "%32,%33,%34,%35,%36,%37,%38,%39,%40,%41,%42,%43,%44,%45,%46,%47,"
        "%48,%49,%50,%51,%52,%53,%54,%55,%56,%57,%58,%59,%60,%61,%62,%63},"
        "{%64,%65,%66,%67}, dsc, 1, 1, 1, 1;\n\t}"
        : "+f"(d[0]), "+f"(d[1]), "+f"(d[2]), "+f"(d[3]), "+f"(d[4]), "+f"(d[5]), "+f"(d[6]), "+f"(d[7]),
          "+f"(d[8]), "+f"(d[9]), "+f"(d[10]), "+f"(d[11]), "+f"(d[12]), "+f"(d[13]), "+f"(d[14]), "+f"(d[15]),
          "+f"(d[16]), "+f"(d[17]), "+f"(d[18]), "+f"(d[19]), "+f"(d[20]), "+f"(d[21]), "+f"(d[22]), "+f"(d[23]),
          "+f"(d[24]), "+f"(d[25]), "+f"(d[26]), "+f"(d[27]), "+f"(d[28]), "+f"(d[29]), "+f"(d[30]), "+f"(d[31]),
          "+f"(d[32]), "+f"(d[33]), "+f"(d[34]), "+f"(d[35]), "+f"(d[36]), "+f"(d[37]), "+f"(d[38]), "+f"(d[39]),
          "+f"(d[40]), "+f"(d[41]), "+f"(d[42]), "+f"(d[43]), "+f"(d[44]), "+f"(d[45]), "+f"(d[46]), "+f"(d[47]),
          "+f"(d[48]), "+f"(d[49]), "+f"(d[50]), "+f"(d[51]), "+f"(d[52]), "+f"(d[53]), "+f"(d[54]), "+f"(d[55]),
          "+f"(d[56]), "+f"(d[57]), "+f"(d[58]), "+f"(d[59]), "+f"(d[60]), "+f"(d[61]), "+f"(d[62]), "+f"(d[63])
        : "r"(a0), "r"(a1), "r"(a2), "r"(a3), "r"(desc_lo), "n"(0x40000000 | (4096 >> 4)));
}

__device__ __forceinline__ float bf16r(float x) {
    uint32_t p;
    asm("cvt.rn.bf16x2.f32 %0, %1, %2;" : "=r"(p) : "f"(x), "f"(0.f));
    return __uint_as_float(p);
}

template <int N> struct IC { static constexpr int value = N; };
struct Frag { uint4 x0, y0, x1, y1; };

__global__ void __launch_bounds__(NTHREADS, 1)
wide_deep_kernel(const int* __restrict__ idx, const __nv_bfloat16* __restrict__ table,
                 const __nv_bfloat16* __restrict__ W1, cudaTextureObject_t idx_tex, uint32_t zero, int tex_off,
                 const __nv_bfloat16* __restrict__ b1, const __nv_bfloat16* __restrict__ x_wide,
                 const __nv_bfloat16* __restrict__ w_wide, const __nv_bfloat16* __restrict__ b_wide,
                 const __nv_bfloat16* __restrict__ W2, const __nv_bfloat16* __restrict__ b2,
                 __nv_bfloat16* __restrict__ out,
                 const __grid_constant__ CUtensorMap tmW, const __grid_constant__ CUtensorMap tmI) {
    extern __shared__ __align__(1024) uint8_t smem_raw[];
    const uint32_t sb = smem_u32(smem_raw);
    const int tid = threadIdx.x;
    const int lane = tid & 31;

    if (tid >= 288) {
        const int c = blockIdx.x & 31;
        if (lane < 16) prefetch_line((const uint8_t*)table + min(c * 16 + lane, 499) * 128);
        if (lane < 8) prefetch_line((const uint8_t*)W1 + (c * 4 + (lane >> 1) + (lane & 1) * ((NSTEP - 2) * 128)) * 128);
    }
    const int warp = __shfl_sync(0xffffffffu, tid >> 5, 0);

    const int asc = blockIdx.x & 1;
    const int pair = blockIdx.x >> 1;
    const int prow0 = pair * BM;

    if (warp == 8) {
        auto load_w = [&](int step, int slot) {
            const int fp = asc ? step : (NSTEP - 2) - step + 2 * (step & 1);
            const uint32_t bar = sb + BAR_FULL + 8 * slot;
            mbar_expect_tx(bar, STAGE_BYTES);
            asm volatile(
                "cp.async.bulk.tensor.5d.shared::cluster.global.mbarrier::complete_tx::bytes "
                "[%0], [%1, {0, 0, %3, 0, 0}], [%2];"
                ::"r"(sb + OFF_W + slot * STAGE_BYTES), "l"(&tmW), "r"(bar), "r"(fp * (4 * FPS)) : "memory");
        };
        auto prefetch_idx = [&](int c) {
            const int f = IDX_F0 + c * IDX_CH;
            asm volatile("cp.async.bulk.prefetch.tensor.2d.L2.global [%0, {%1, %2}];"
                         ::"l"(&tmI), "r"(asc ? kF + f : kF - f - IDX_CH), "r"(prow0) : "memory");
        };
        if (elect()) {
            asm volatile("prefetch.tensormap [%0];" ::"l"(&tmW) : "memory");
            mbar_init(sb + BAR_TBL, 1);
            mbar_init(sb + BAR_FULL, 1);
            mbar_init(sb + BAR_B1, 1);
            mbar_init_fence();
            bulk_load(sb + OFF_B1, b1, 256, sb + BAR_B1);
            load_w(0, 0);
            bulk_load(sb + OFF_TBL, table, TBL_BYTES, sb + BAR_TBL);
            asm volatile("prefetch.tensormap [%0];" ::"l"(&tmI) : "memory");
            for (int s = 1; s < NST; s++) mbar_init(sb + BAR_FULL + 8 * s, 1);
            for (int s = 0; s < NST; s++) mbar_init(sb + BAR_EMPTY + 8 * s, 2);
            mbar_init(sb + BAR_X, 1);
            mbar_init(sb + BAR_EPI, 32);
            mbar_init_fence();
        }
        __syncthreads();
        if (elect()) {
            mbar_wait(sb + BAR_FULL, 0);
            load_w(1, 1);
            mbar_wait(sb + BAR_TBL, 0);
            for (int s = 2; s < NST; s++) load_w(s, s);
            prefetch_idx(0);
            constexpr int MID = (NSTEP - 2 * NST) * STAGE_BYTES / NCTA;
            asm volatile("cp.async.bulk.prefetch.L2.global [%0], %1;"
                         ::"l"((const uint8_t*)W1 + NST * STAGE_BYTES + blockIdx.x * MID), "n"(MID) : "memory");
            bulk_load(sb + OFF_X, (const uint8_t*)x_wide + pair * X_BYTES, X_BYTES, sb + BAR_X);
            int slot = 0, nextc = 1;
            uint32_t ph = 0;
#pragma unroll 1
            for (int step = NST; step < NSTEP; step++) {
                mbar_wait(sb + BAR_EMPTY + 8 * slot, ph);
                load_w(step, slot);
                if (++slot == NST) { slot = 0; ph ^= 1; }
                if (IDX_F0 + nextc * IDX_CH < kF && step == NST + nextc * 6) prefetch_idx(nextc++);
            }
        }
    } else if (warp == 9) {
        __syncthreads();
        if (lane < 2 * NST) {
            const int i = blockIdx.x * NST + (lane >> 1);
            prefetch_line((const uint8_t*)W1 + ((lane & 1) ? NSTEP * 128 - 1 - i : i) * 128);
        }
        {
            const int tc = tex_off + (prow0 + lane) * PITCH4 + (kF / 4 - 1) + (asc ? 2 : -1);
            uint32_t x = 0;
#pragma unroll
            for (int r = 0; r < 4; r++) x |= tex128(idx_tex, tc + 32 * r * PITCH4).x;
            if ((x & zero) != 0) __trap();
        }
        mbar_wait(sb + BAR_X, 0);
#pragma unroll
        for (int h = 0; h < 2; h++) {
            const int w = lane + 32 * h;
            ((uint32_t*)(smem_raw + OFF_W2))[(w & 48) + (w & 3) * 4 + ((w >> 2) & 3)] = __ldg((const uint32_t*)W2 + w);
        }
        const float wl = (lane >= asc && lane < kNd + asc) ? __bfloat162float(w_wide[lane - asc]) : 0.f;
        const float bw = __bfloat162float(b_wide[0]);
        const float b2v = __bfloat162float(b2[0]);
        float wt[14];
#pragma unroll
        for (int j = 0; j < 14; j++) wt[j] = __shfl_sync(0xffffffffu, wl, j);
#pragma unroll
        for (int r = 0; r < 4; r++) {
            const uint32_t* x = (const uint32_t*)(smem_raw + OFF_X) + (lane + 32 * r) * kNd + 6 * asc;
            float s = 0.f;
#pragma unroll
            for (int j = 0; j < 7; j++) {
                uint32_t v = x[j];
                if (j == 0 && asc) v &= 0xffff0000u;
                if (j == 6 && !asc) v &= 0x0000ffffu;
                s = fmaf(__uint_as_float(v << 16), wt[2 * j], s);
                s = fmaf(__uint_as_float(v & 0xffff0000u), wt[2 * j + 1], s);
            }
            ((float2*)(smem_raw + OFF_WIDE))[lane + 32 * r] = make_float2(bf16r(bf16r(s) + bw), b2v);
        }
        mbar_arrive(sb + BAR_EPI);
    } else {
        const int q = lane & 3;
        const int r0 = warp * 16 + (lane >> 2);
        const int tstep = asc ? 1 : -1;
        int tcoord = (prow0 + r0) * PITCH4 + (kF / 4 - 1) + asc;
        const uint4 f0 = ldg128((const uint4*)idx + tcoord), f1 = ldg128((const uint4*)idx + tcoord + 8 * PITCH4);
        tcoord += tstep + tex_off;
        __syncthreads();

        float acc[64];
        mbar_wait(sb + BAR_B1, 0);
#pragma unroll
        for (int n = 0; n < 16; n++) {
            uint32_t v;
            asm volatile("ld.shared.u32 %0, [%1];" : "=r"(v) : "r"(sb + OFF_B1 + 16 * n + 4 * q) : "memory");
            acc[4 * n] = acc[4 * n + 2] = __uint_as_float(v << 16);
            acc[4 * n + 1] = acc[4 * n + 3] = __uint_as_float(v & 0xffff0000u);
        }
#pragma unroll
        for (int i = 0; i < 64; i++) asm volatile("" : "+f"(acc[i])::"memory");

        const uint64_t outp = (uint64_t)(out + 2 * (prow0 + r0 + 8 * (q & 1)) + asc);
        const uint32_t out_lo = pin((uint32_t)outp, lane), out_hi = pin((uint32_t)(outp >> 32), lane);
        const uint32_t wide_addr = pin(sb + OFF_WIDE + (r0 + 8 * (q & 1)) * 8, lane);
        const uint32_t tbase = pin(sb + OFF_TBL + q * 16, lane);
        auto gaddr = [&](uint32_t v) -> uint32_t { return tbase + v * 64; };
        const bool signaller = (tid & 127) == 0;
        const uint32_t desc0 = (((sb + OFF_W) & 0x3FFFF) >> 4) | ((8192 >> 4) << 16);

        mbar_wait(sb + BAR_FULL, 0);
        uint32_t ga[8] = {gaddr(f0.x), gaddr(f1.x), gaddr(f0.y), gaddr(f1.y),
                          gaddr(f0.z), gaddr(f1.z), gaddr(f0.w), gaddr(f1.w)};
#pragma unroll
        for (int i = 0; i < 8; i++) ga[i] = pin(ga[i], lane);
        mbar_wait(sb + BAR_TBL, 0);

        Frag A[2];
        uint4 i0 = f0, i1 = f1, n0, n1;
        bool ok;
        {
            Frag t;
            Frag& a = A[0];
            const uint4 x0 = lds128(ga[0]), y0 = lds128(ga[1]);
            __syncwarp();
            const uint4 x1 = lds128(ga[2]), y1 = lds128(ga[3]);
            __syncwarp();
            a.x0 = copy4(x0, zero); a.y0 = copy4(y0, zero);
            wgmma_fence();
            wgmma_rs(acc, a.x0.x, a.y0.x, a.x0.z, a.y0.z, desc0);
            __syncwarp();
            t.x0 = lds128(ga[4]);
            wgmma_rs(acc, a.x0.y, a.y0.y, a.x0.w, a.y0.w, desc0 + 128);
            wgmma_commit();
            wgmma_wait<1>();
            const uint32_t z1 = zero & mbar_test(sb + BAR_FULL, 0);
            t.y0 = lds128(ga[5]);
            n0 = tex128(idx_tex, tcoord);
            n1 = tex128(idx_tex, tcoord + 8 * PITCH4);
            tcoord += tstep;
            a.x1 = copy4(x1, z1); a.y1 = copy4(y1, z1);
            wgmma_fence();
            wgmma_rs(acc, a.x1.x, a.y1.x, a.x1.z, a.y1.z, desc0 + 64);
            __syncwarp();
            t.x1 = lds128(ga[6]);
            t.y1 = lds128(ga[7]);
            wgmma_rs(acc, a.x1.y, a.y1.y, a.x1.w, a.y1.w, desc0 + 192);
            wgmma_commit();
            wgmma_wait<1>();
            const uint32_t okv = mbar_test(sb + BAR_FULL + 8, 0);
            ok = okv != 0;
            const uint32_t z2 = zero & okv;
            A[1].x0 = copy4(t.x0, z2); A[1].y0 = copy4(t.y0, z2); A[1].x1 = copy4(t.x1, z2); A[1].y1 = copy4(t.y1, z2);
        }
        auto stage = [&](auto uc, int o) {
            constexpr int u = decltype(uc)::value;
            constexpr int slot = u % NST;
            const Frag& a = A[u & 1];
            if (u == UN - 3 && o + 1 == NOUT) mbar_wait(sb + BAR_EPI, 0);
            if (!ok) mbar_wait(sb + BAR_FULL + 8 * slot, u / NST);
            uint32_t g0, g1, g2, g3;
            if ((u & 1) == 0) {
                g0 = gaddr(i0.z); g1 = gaddr(i1.z); g2 = gaddr(i0.w); g3 = gaddr(i1.w);
            } else {
                i0 = n0; i1 = n1;
                g0 = gaddr(i0.x); g1 = gaddr(i1.x); g2 = gaddr(i0.y); g3 = gaddr(i1.y);
                if (u < UN - 3 || o + 1 < NOUT) {
                    n0 = tex128(idx_tex, tcoord);
                    n1 = tex128(idx_tex, tcoord + 8 * PITCH4);
                    tcoord += tstep;
                } else if (u == UN - 3) {
                    n0.x = kV; n1.x = kV + 1; n0.y = kV + 2; n1.y = kV + 3;
                }
            }
            const uint32_t d = desc0 + slot * (STAGE_BYTES >> 4);
            Frag t;
            wgmma_fence();
            t.x0 = lds128(g0);
            wgmma_rs(acc, a.x0.x, a.y0.x, a.x0.z, a.y0.z, d);
            __syncwarp();
            t.y0 = lds128(g1);
            wgmma_rs(acc, a.x0.y, a.y0.y, a.x0.w, a.y0.w, d + 128);
            __syncwarp();
            t.x1 = lds128(g2);
            wgmma_rs(acc, a.x1.x, a.y1.x, a.x1.z, a.y1.z, d + 64);
            __syncwarp();
            t.y1 = lds128(g3);
            wgmma_rs(acc, a.x1.y, a.y1.y, a.x1.w, a.y1.w, d + 192);
            wgmma_commit();
            wgmma_wait<1>();
            ok = mbar_test(sb + BAR_FULL + 8 * ((u + 1) % NST), ((u + 1) / NST) & 1) != 0;
            if ((u <= UN - NST || o + 1 < NOUT) && signaller) mbar_arrive(sb + BAR_EMPTY + 8 * ((u + NST - 1) % NST));
            Frag& an = A[(u + 1) & 1];
            an.x0 = copy4(t.x0, zero); an.y0 = copy4(t.y0, zero); an.x1 = copy4(t.x1, zero); an.y1 = copy4(t.y1, zero);
        };
#pragma unroll 1
        for (int o = 0;;) {
            stage(IC<1>{}, o); stage(IC<2>{}, o); stage(IC<3>{}, o);
            stage(IC<4>{}, o); stage(IC<5>{}, o); stage(IC<6>{}, o);
            stage(IC<7>{}, o); stage(IC<8>{}, o); stage(IC<9>{}, o);
            if (++o == NOUT) break;
            stage(IC<0>{}, o);
        }

        const uint32_t w2[16] = {A[0].x0.x, A[0].x0.y, A[0].x0.z, A[0].x0.w, A[0].y0.x, A[0].y0.y, A[0].y0.z, A[0].y0.w,
                                 A[0].x1.x, A[0].x1.y, A[0].x1.z, A[0].x1.w, A[0].y1.x, A[0].y1.y, A[0].y1.z, A[0].y1.w};
        float wide, b2f;
        asm volatile("ld.shared.v2.f32 {%0,%1}, [%2];" : "=f"(wide), "=f"(b2f) : "r"(wide_addr));
        wgmma_wait<0>();
#pragma unroll
        for (int i = 0; i < 64; i++) asm volatile("" : "+f"(acc[i])::"memory");
        float cc[4][4] = {};
#pragma unroll
        for (int s = 0; s < 8; s++) {
            uint32_t h[4];
#pragma unroll
            for (int i = 0; i < 4; i++)
                asm("cvt.rn.relu.bf16x2.f32 %0, %1, %2;" : "=r"(h[i]) : "f"(acc[8 * s + 2 * i + 1]), "f"(acc[8 * s + 2 * i]));
            float* c = cc[s & 3];
            asm volatile(
                "mma.sync.aligned.m16n8k16.row.col.f32.bf16.bf16.f32 {%0,%1,%2,%3}, {%4,%5,%6,%7}, {%8,%9}, {%0,%1,%2,%3};"
                : "+f"(c[0]), "+f"(c[1]), "+f"(c[2]), "+f"(c[3])
                : "r"(h[0]), "r"(h[1]), "r"(h[2]), "r"(h[3]), "r"(w2[2 * s]), "r"(w2[2 * s + 1]));
        }
        const bool hi = (tbase & 16) != 0;
        const float deep = hi ? (cc[0][2] + cc[1][2]) + (cc[2][2] + cc[3][2])
                              : (cc[0][0] + cc[1][0]) + (cc[2][0] + cc[3][0]);
        const float z = bf16r(wide + bf16r(bf16r(deep) + b2f));
        float e, p;
        asm("ex2.approx.ftz.f32 %0, %1;" : "=f"(e) : "f"(z * -1.4426950408889634f));
        asm("rcp.approx.ftz.f32 %0, %1;" : "=f"(p) : "f"(1.f + e));
        if (!(tbase & 32))
            asm volatile("st.global.b16 [%0], %1;" ::"l"(((uint64_t)out_hi << 32) | out_lo),
                         "h"(__bfloat16_as_ushort(__float2bfloat16_rn(p))) : "memory");
    }
}

typedef CUresult (*EncodeTiledFn)(CUtensorMap*, CUtensorMapDataType, cuuint32_t, void*, const cuuint64_t*,
                                  const cuuint64_t*, const cuuint32_t*, const cuuint32_t*, CUtensorMapInterleave,
                                  CUtensorMapSwizzle, CUtensorMapL2promotion, CUtensorMapFloatOOBfill);

}

extern "C" void kernel_launch(void* const* d_in, const int* in_sizes, int n_in, void* d_out, int out_size) {
    using namespace wd;
    (void)in_sizes; (void)n_in; (void)out_size;
    static EncodeTiledFn encode = nullptr;
    static cudaTextureObject_t idx_tex = 0;
    static const void* idx_tex_ptr = nullptr;
    if (!encode) {
        void* fn = nullptr;
        cudaDriverEntryPointQueryResult qr;
        cudaGetDriverEntryPoint("cuTensorMapEncodeTiled", &fn, cudaEnableDefault, &qr);
        encode = (EncodeTiledFn)fn;
        cudaFuncSetAttribute(wide_deep_kernel, cudaFuncAttributeMaxDynamicSharedMemorySize, SMEM_BYTES);
    }
    const size_t tex_pad = (size_t)d_in[0] & 511;
    if (idx_tex_ptr != d_in[0]) {
        cudaResourceDesc rd = {};
        rd.resType = cudaResourceTypeLinear;
        rd.res.linear.devPtr = (char*)d_in[0] - tex_pad;
        rd.res.linear.desc = cudaCreateChannelDesc(32, 32, 32, 32, cudaChannelFormatKindSigned);
        rd.res.linear.sizeInBytes = (size_t)kB * kF * 4 + tex_pad;
        cudaTextureDesc td = {};
        td.readMode = cudaReadModeElementType;
        cudaCreateTextureObject(&idx_tex, &rd, &td, nullptr);
        idx_tex_ptr = d_in[0];
    }

    CUtensorMap tmW, tmI;
    {
        cuuint64_t dims[5] = {64, 2, 4 * (cuuint64_t)kF, 4, 2};
        cuuint64_t strides[4] = {256, 8 * 256, 2 * 256, 128};
        cuuint32_t box[5] = {64, 2, 4 * FPS, 4, 2};
        cuuint32_t es[5] = {1, 1, 1, 1, 1};
        encode(&tmW, CU_TENSOR_MAP_DATA_TYPE_BFLOAT16, 5, d_in[5], dims, strides, box, es,
               CU_TENSOR_MAP_INTERLEAVE_NONE, CU_TENSOR_MAP_SWIZZLE_128B, CU_TENSOR_MAP_L2_PROMOTION_L2_256B,
               CU_TENSOR_MAP_FLOAT_OOB_FILL_NONE);
    }
    {
        cuuint64_t dims[2] = {2 * (cuuint64_t)kF, (cuuint64_t)kB / 2};
        cuuint64_t strides[1] = {(cuuint64_t)kF * 8};
        cuuint32_t box[2] = {IDX_CH, BM};
        cuuint32_t es[2] = {1, 1};
        encode(&tmI, CU_TENSOR_MAP_DATA_TYPE_INT32, 2, d_in[0], dims, strides, box, es,
               CU_TENSOR_MAP_INTERLEAVE_NONE, CU_TENSOR_MAP_SWIZZLE_NONE, CU_TENSOR_MAP_L2_PROMOTION_NONE,
               CU_TENSOR_MAP_FLOAT_OOB_FILL_NONE);
    }
    wide_deep_kernel<<<NCTA, NTHREADS, SMEM_BYTES, cudaStreamPerThread>>>(
        (const int*)d_in[0], (const __nv_bfloat16*)d_in[1], (const __nv_bfloat16*)d_in[5], idx_tex, 0u, (int)(tex_pad / 16),
        (const __nv_bfloat16*)d_in[6], (const __nv_bfloat16*)d_in[2], (const __nv_bfloat16*)d_in[3],
        (const __nv_bfloat16*)d_in[4], (const __nv_bfloat16*)d_in[7], (const __nv_bfloat16*)d_in[8],
        (__nv_bfloat16*)d_out, tmW, tmI);
}
```

```cpp
#include <cuda_runtime.h>
#include <cuda_bf16.h>
#include <cuda.h>
#include <stdint.h>

namespace wd {

constexpr int kB = 16384, kF = 100, kD = 32, kH = 128, kV = 1000, kNd = 13;
constexpr int BM = 128;
constexpr int NCTA = kB / BM;
constexpr int FPS = 2;
constexpr int STAGE_BYTES = FPS * kD * kH * 2;
constexpr int NST = 5;
constexpr int NSTEP = kF / FPS;
constexpr int UN = 2 * NST;
constexpr int NOUT = NSTEP / UN;
constexpr int IDX_F0 = 12;
constexpr int IDX_CH = 24;
constexpr int PITCH4 = kF / 2;
constexpr int TBL_BYTES = kV * kD * 2;
constexpr int X_BYTES = 2 * BM * kNd * 2;

constexpr int OFF_W = 0;
constexpr int OFF_TBL = OFF_W + NST * STAGE_BYTES;
constexpr int OFF_W2 = OFF_TBL + TBL_BYTES;
constexpr int OFF_B1 = OFF_W2 + 256;
constexpr int OFF_WIDE = OFF_B1 + 256;
constexpr int OFF_X = OFF_WIDE + 8 * BM;
constexpr int BAR_FULL = OFF_X + X_BYTES;
constexpr int BAR_EMPTY = BAR_FULL + 8 * NST;
constexpr int BAR_TBL = BAR_EMPTY + 8 * NST;
constexpr int BAR_B1 = BAR_TBL + 8;
constexpr int BAR_X = BAR_B1 + 8;
constexpr int BAR_EPI = BAR_X + 8;
constexpr int SMEM_BYTES = BAR_EPI + 8;
static_assert(SMEM_BYTES <= 232448, "smem");
static_assert(OFF_TBL % 64 == 0 && OFF_B1 % 16 == 0 && OFF_X % 16 == 0 && BAR_FULL % 8 == 0, "align");

constexpr int NTHREADS = 320;

__device__ __forceinline__ uint32_t smem_u32(const void* p) { return (uint32_t)__cvta_generic_to_shared(p); }
__device__ __forceinline__ void mbar_init(uint32_t bar, uint32_t cnt) {
    asm volatile("mbarrier.init.shared::cta.b64 [%0], %1;" ::"r"(bar), "r"(cnt) : "memory");
}
__device__ __forceinline__ void mbar_init_fence() {
    asm volatile("fence.mbarrier_init.release.cluster;" ::: "memory");
}
__device__ __forceinline__ void mbar_expect_tx(uint32_t bar, uint32_t bytes) {
    asm volatile("mbarrier.arrive.expect_tx.shared::cta.b64 _, [%0], %1;" ::"r"(bar), "r"(bytes) : "memory");
}
__device__ __forceinline__ void mbar_arrive(uint32_t bar) {
    asm volatile("mbarrier.arrive.shared::cta.b64 _, [%0];" ::"r"(bar) : "memory");
}
__device__ __forceinline__ uint32_t mbar_test(uint32_t bar, uint32_t parity) {
    uint32_t ok;
    asm volatile(
        "{\n\t.reg .pred p;\n\t"
        "mbarrier.test_wait.parity.shared::cta.b64 p, [%1], %2;\n\t"
        "selp.u32 %0, 1, 0, p;\n\t}"
        : "=r"(ok) : "r"(bar), "r"(parity) : "memory");
    return ok;
}
__device__ __forceinline__ void mbar_wait(uint32_t bar, uint32_t parity) {
    asm volatile(
        "{\n\t.reg .pred p;\n\t.reg .u32 n;\n\t"
        "mov.u32 n, 0;\n\t"
        "W_LOOP:\n\t"
        "mbarrier.try_wait.parity.shared::cta.b64 p, [%0], %1;\n\t"
        "@p bra W_DONE;\n\t"
        "add.u32 n, n, 1;\n\t"
        "setp.lt.u32 p, n, 4194304;\n\t"
        "@p bra W_LOOP;\n\t"
        "trap;\n\t"
        "W_DONE:\n\t}"
        ::"r"(bar), "r"(parity) : "memory");
}
__device__ __forceinline__ void bulk_load(uint32_t dst, const void* src, uint32_t bytes, uint32_t bar) {
    mbar_expect_tx(bar, bytes);
    asm volatile("cp.async.bulk.shared::cluster.global.mbarrier::complete_tx::bytes [%0], [%1], %2, [%3];"
                 ::"r"(dst), "l"(src), "r"(bytes), "r"(bar) : "memory");
}
__device__ __forceinline__ void prefetch_line(const void* p) {
    asm volatile("prefetch.global.L2 [%0];" ::"l"(p) : "memory");
}
__device__ __forceinline__ uint4 lds128(uint32_t addr) {
    uint4 v;
    asm volatile("ld.shared.v4.u32 {%0,%1,%2,%3}, [%4];" : "=r"(v.x), "=r"(v.y), "=r"(v.z), "=r"(v.w) : "r"(addr));
    return v;
}
__device__ __forceinline__ uint4 ldg128(const uint4* p) {
    uint4 v;
    asm volatile("ld.global.v4.u32 {%0,%1,%2,%3}, [%4];"
                 : "=r"(v.x), "=r"(v.y), "=r"(v.z), "=r"(v.w) : "l"(p) : "memory");
    return v;
}
__device__ __forceinline__ uint4 tex128(cudaTextureObject_t t, int i) {
    uint4 v;
    asm volatile("tex.1d.v4.s32.s32 {%0,%1,%2,%3}, [%4, {%5}];"
                 : "=r"(v.x), "=r"(v.y), "=r"(v.z), "=r"(v.w) : "l"(t), "r"(i));
    return v;
}
__device__ __forceinline__ void cta_sync() { asm volatile("barrier.sync 1, %0;" ::"n"(NTHREADS) : "memory"); }
__device__ __forceinline__ bool elect() {
    uint32_t p;
    asm volatile("{\n\t.reg .pred P;\n\telect.sync _|P, 0xffffffff;\n\tselp.u32 %0, 1, 0, P;\n\t}" : "=r"(p));
    return p != 0;
}
__device__ __forceinline__ uint4 copy4(uint4 t, uint32_t z) {
    uint4 r;
    asm volatile("xor.b32 %0, %1, %2;" : "=r"(r.x) : "r"(t.x), "r"(z));
    asm volatile("xor.b32 %0, %1, %2;" : "=r"(r.y) : "r"(t.y), "r"(z));
    asm volatile("xor.b32 %0, %1, %2;" : "=r"(r.z) : "r"(t.z), "r"(z));
    asm volatile("xor.b32 %0, %1, %2;" : "=r"(r.w) : "r"(t.w), "r"(z));
    return r;
}
__device__ __forceinline__ uint32_t pin(uint32_t v, int lane) { return __shfl_sync(0xffffffffu, v, lane); }

__device__ __forceinline__ void wgmma_fence() { asm volatile("wgmma.fence.sync.aligned;" ::: "memory"); }
__device__ __forceinline__ void wgmma_commit() { asm volatile("wgmma.commit_group.sync.aligned;" ::: "memory"); }
template <int N>
__device__ __forceinline__ void wgmma_wait() { asm volatile("wgmma.wait_group.sync.aligned %0;" ::"n"(N) : "memory"); }

__device__ __forceinline__ void wgmma_rs(float (&d)[64], uint32_t a0, uint32_t a1, uint32_t a2, uint32_t a3,
                                         uint32_t desc_lo) {
    asm volatile(
        "{\n\t.reg .b64 dsc;\n\t"
        "mov.b64 dsc, {%68, %69};\n\t"
        "wgmma.mma_async.sync.aligned.m64n128k16.f32.bf16.bf16 "
        "{%0,%1,%2,%3,%4,%5,%6,%7,%8,%9,%10,%11,%12,%13,%14,%15,"
        "%16,%17,%18,%19,%20,%21,%22,%23,%24,%25,%26,%27,%28,%29,%30,%31,"
        "%32,%33,%34,%35,%36,%37,%38,%39,%40,%41,%42,%43,%44,%45,%46,%47,"
        "%48,%49,%50,%51,%52,%53,%54,%55,%56,%57,%58,%59,%60,%61,%62,%63},"
        "{%64,%65,%66,%67}, dsc, 1, 1, 1, 1;\n\t}"
        : "+f"(d[0]), "+f"(d[1]), "+f"(d[2]), "+f"(d[3]), "+f"(d[4]), "+f"(d[5]), "+f"(d[6]), "+f"(d[7]),
          "+f"(d[8]), "+f"(d[9]), "+f"(d[10]), "+f"(d[11]), "+f"(d[12]), "+f"(d[13]), "+f"(d[14]), "+f"(d[15]),
          "+f"(d[16]), "+f"(d[17]), "+f"(d[18]), "+f"(d[19]), "+f"(d[20]), "+f"(d[21]), "+f"(d[22]), "+f"(d[23]),
          "+f"(d[24]), "+f"(d[25]), "+f"(d[26]), "+f"(d[27]), "+f"(d[28]), "+f"(d[29]), "+f"(d[30]), "+f"(d[31]),
          "+f"(d[32]), "+f"(d[33]), "+f"(d[34]), "+f"(d[35]), "+f"(d[36]), "+f"(d[37]), "+f"(d[38]), "+f"(d[39]),
          "+f"(d[40]), "+f"(d[41]), "+f"(d[42]), "+f"(d[43]), "+f"(d[44]), "+f"(d[45]), "+f"(d[46]), "+f"(d[47]),
          "+f"(d[48]), "+f"(d[49]), "+f"(d[50]), "+f"(d[51]), "+f"(d[52]), "+f"(d[53]), "+f"(d[54]), "+f"(d[55]),
          "+f"(d[56]), "+f"(d[57]), "+f"(d[58]), "+f"(d[59]), "+f"(d[60]), "+f"(d[61]), "+f"(d[62]), "+f"(d[63])
        : "r"(a0), "r"(a1), "r"(a2), "r"(a3), "r"(desc_lo), "n"(0x40000000 | (4096 >> 4)));
}

__device__ __forceinline__ float bf16r(float x) {
    uint32_t p;
    asm("cvt.rn.bf16x2.f32 %0, %1, %2;" : "=r"(p) : "f"(x), "f"(0.f));
    return __uint_as_float(p);
}

template <int N> struct IC { static constexpr int value = N; };
struct Frag { uint4 x0, y0, x1, y1; };

__global__ void __launch_bounds__(NTHREADS, 1)
wide_deep_kernel(const int* __restrict__ idx, const __nv_bfloat16* __restrict__ table,
                 const __nv_bfloat16* __restrict__ W1, cudaTextureObject_t idx_tex, uint32_t zero,
                 const __nv_bfloat16* __restrict__ b1, const __nv_bfloat16* __restrict__ x_wide,
                 const __nv_bfloat16* __restrict__ w_wide, const __nv_bfloat16* __restrict__ b_wide,
                 const __nv_bfloat16* __restrict__ W2, const __nv_bfloat16* __restrict__ b2,
                 __nv_bfloat16* __restrict__ out,
                 const __grid_constant__ CUtensorMap tmW, const __grid_constant__ CUtensorMap tmI) {
    extern __shared__ __align__(1024) uint8_t smem_raw[];
    const uint32_t sb = smem_u32(smem_raw);
    const int tid = threadIdx.x;
    const int lane = tid & 31;

    if (tid >= 288) {
        const int c = blockIdx.x & 31;
        if (lane < 16) prefetch_line((const uint8_t*)table + min(c * 16 + lane, 499) * 128);
        if (lane < 8) prefetch_line((const uint8_t*)W1 + (c * 4 + (lane >> 1) + (lane & 1) * ((NSTEP - 2) * 128)) * 128);
    }
    const int warp = __shfl_sync(0xffffffffu, tid >> 5, 0);

    const int asc = blockIdx.x & 1;
    const int pair = blockIdx.x >> 1;
    const int prow0 = pair * BM;

    if (warp == 8) {
        auto load_w = [&](int step, int slot) {
            const int fp = asc ? step : (NSTEP - 2) - step + 2 * (step & 1);
            const uint32_t bar = sb + BAR_FULL + 8 * slot;
            mbar_expect_tx(bar, STAGE_BYTES);
            asm volatile(
                "cp.async.bulk.tensor.5d.shared::cluster.global.mbarrier::complete_tx::bytes "
                "[%0], [%1, {0, 0, %3, 0, 0}], [%2];"
                ::"r"(sb + OFF_W + slot * STAGE_BYTES), "l"(&tmW), "r"(bar), "r"(fp * (4 * FPS)) : "memory");
        };
        auto prefetch_idx = [&](int c) {
            const int f = IDX_F0 + c * IDX_CH;
            asm volatile("cp.async.bulk.prefetch.tensor.2d.L2.global [%0, {%1, %2}];"
                         ::"l"(&tmI), "r"(asc ? kF + f : kF - f - IDX_CH), "r"(prow0) : "memory");
        };
        if (elect()) {
            asm volatile("prefetch.tensormap [%0];" ::"l"(&tmW) : "memory");
            mbar_init(sb + BAR_TBL, 1);
            mbar_init(sb + BAR_FULL, 1);
            mbar_init(sb + BAR_B1, 1);
            mbar_init_fence();
            bulk_load(sb + OFF_B1, b1, 256, sb + BAR_B1);
            load_w(0, 0);
            bulk_load(sb + OFF_TBL, table, TBL_BYTES, sb + BAR_TBL);
            asm volatile("prefetch.tensormap [%0];" ::"l"(&tmI) : "memory");
            for (int s = 1; s < NST; s++) mbar_init(sb + BAR_FULL + 8 * s, 1);
            for (int s = 0; s < NST; s++) mbar_init(sb + BAR_EMPTY + 8 * s, 2);
            mbar_init(sb + BAR_X, 1);
            mbar_init(sb + BAR_EPI, 32);
            mbar_init_fence();
        }
        cta_sync();
        if (elect()) {
            mbar_wait(sb + BAR_FULL, 0);
            load_w(1, 1);
            mbar_wait(sb + BAR_TBL, 0);
            for (int s = 2; s < NST; s++) load_w(s, s);
            prefetch_idx(0);
            constexpr int MID = (NSTEP - 2 * NST) * STAGE_BYTES / NCTA;
            asm volatile("cp.async.bulk.prefetch.L2.global [%0], %1;"
                         ::"l"((const uint8_t*)W1 + NST * STAGE_BYTES + blockIdx.x * MID), "n"(MID) : "memory");
            bulk_load(sb + OFF_X, (const uint8_t*)x_wide + pair * X_BYTES, X_BYTES, sb + BAR_X);
            int slot = 0, nextc = 1;
            uint32_t ph = 0;
#pragma unroll 1
            for (int step = NST; step < NSTEP; step++) {
                mbar_wait(sb + BAR_EMPTY + 8 * slot, ph);
                load_w(step, slot);
                if (++slot == NST) { slot = 0; ph ^= 1; }
                if (IDX_F0 + nextc * IDX_CH < kF && step == NST + nextc * 6) prefetch_idx(nextc++);
            }
        }
    } else if (warp == 9) {
        if (lane < 2 * NST) {
            const int i = blockIdx.x * NST + (lane >> 1);
            prefetch_line((const uint8_t*)W1 + ((lane & 1) ? NSTEP * 128 - 1 - i : i) * 128);
        }
        {
            const int tc = (prow0 + lane) * PITCH4 + (kF / 4 - 1) + (asc ? 2 : -1);
            uint4 v[4];
#pragma unroll
            for (int r = 0; r < 4; r++) v[r] = tex128(idx_tex, tc + 32 * r * PITCH4);
            cta_sync();
            if (((v[0].x | v[1].x | v[2].x | v[3].x) & zero) != 0) __trap();
        }
        mbar_wait(sb + BAR_X, 0);
#pragma unroll
        for (int h = 0; h < 2; h++) {
            const int w = lane + 32 * h;
            ((uint32_t*)(smem_raw + OFF_W2))[(w & 48) + (w & 3) * 4 + ((w >> 2) & 3)] = __ldg((const uint32_t*)W2 + w);
        }
        const float wl = (lane >= asc && lane < kNd + asc) ? __bfloat162float(w_wide[lane - asc]) : 0.f;
        const float bw = __bfloat162float(b_wide[0]);
        const float b2v = __bfloat162float(b2[0]);
        float wt[14];
#pragma unroll
        for (int j = 0; j < 14; j++) wt[j] = __shfl_sync(0xffffffffu, wl, j);
#pragma unroll
        for (int r = 0; r < 4; r++) {
            const uint32_t* x = (const uint32_t*)(smem_raw + OFF_X) + (lane + 32 * r) * kNd + 6 * asc;
            float s = 0.f;
#pragma unroll
            for (int j = 0; j < 7; j++) {
                uint32_t v = x[j];
                if (j == 0 && asc) v &= 0xffff0000u;
                if (j == 6 && !asc) v &= 0x0000ffffu;
                s = fmaf(__uint_as_float(v << 16), wt[2 * j], s);
                s = fmaf(__uint_as_float(v & 0xffff0000u), wt[2 * j + 1], s);
            }
            ((float2*)(smem_raw + OFF_WIDE))[lane + 32 * r] = make_float2(bf16r(bf16r(s) + bw), b2v);
        }
        mbar_arrive(sb + BAR_EPI);
    } else {
        const int q = lane & 3;
        const int r0 = warp * 16 + (lane >> 2);
        const int tstep = asc ? 1 : -1;
        int tcoord = (prow0 + r0) * PITCH4 + (kF / 4 - 1) + asc;
        const uint4 f0 = ldg128((const uint4*)idx + tcoord), f1 = ldg128((const uint4*)idx + tcoord + 8 * PITCH4);
        tcoord += tstep;
        cta_sync();

        float acc[64];
        mbar_wait(sb + BAR_B1, 0);
        uint32_t bv[16];
#pragma unroll
        for (int n = 0; n < 16; n++) {
            uint16_t h;
            asm volatile("ld.shared.u16 %0, [%1];" : "=h"(h) : "r"(sb + OFF_B1 + 16 * n + 2 * (lane >> 2)) : "memory");
            bv[n] = q == 0 ? h : 0;
        }
        const uint32_t one = q == 0 ? 0x3f80u : 0u;
#pragma unroll
        for (int n = 0; n < 16; n++)
            asm volatile("mma.sync.aligned.m16n8k8.row.col.f32.bf16.bf16.f32 {%0,%1,%2,%3}, {%4,%4}, {%5}, {%6,%6,%6,%6};"
                         : "=f"(acc[4 * n]), "=f"(acc[4 * n + 1]), "=f"(acc[4 * n + 2]), "=f"(acc[4 * n + 3])
                         : "r"(one), "r"(bv[n]), "f"(0.f));
#pragma unroll
        for (int i = 0; i < 64; i++) asm volatile("" : "+f"(acc[i])::"memory");

        const uint64_t outp = (uint64_t)(out + 2 * (prow0 + r0 + 8 * (q & 1)) + asc);
        const uint32_t out_lo = pin((uint32_t)outp, lane), out_hi = pin((uint32_t)(outp >> 32), lane);
        const uint32_t wide_addr = pin(sb + OFF_WIDE + (r0 + 8 * (q & 1)) * 8, lane);
        const uint32_t tbase = pin(sb + OFF_TBL + q * 16, lane);
        auto gaddr = [&](uint32_t v) -> uint32_t { return tbase + v * 64; };
        const bool signaller = (tid & 127) == 0;
        const uint32_t desc0 = (((sb + OFF_W) & 0x3FFFF) >> 4) | ((8192 >> 4) << 16);

        mbar_wait(sb + BAR_FULL, 0);
        uint32_t ga[8] = {gaddr(f0.x), gaddr(f1.x), gaddr(f0.y), gaddr(f1.y),
                          gaddr(f0.z), gaddr(f1.z), gaddr(f0.w), gaddr(f1.w)};
#pragma unroll
        for (int i = 0; i < 8; i++) ga[i] = pin(ga[i], lane);
        mbar_wait(sb + BAR_TBL, 0);

        Frag A[2];
        uint4 i0 = f0, i1 = f1, n0, n1;
        bool ok;
        {
            Frag t;
            Frag& a = A[0];
            const uint4 x0 = lds128(ga[0]), y0 = lds128(ga[1]);
            __syncwarp();
            const uint4 x1 = lds128(ga[2]), y1 = lds128(ga[3]);
            __syncwarp();
            a.x0 = copy4(x0, zero); a.y0 = copy4(y0, zero);
            wgmma_fence();
            wgmma_rs(acc, a.x0.x, a.y0.x, a.x0.z, a.y0.z, desc0);
            __syncwarp();
            t.x0 = lds128(ga[4]);
            wgmma_rs(acc, a.x0.y, a.y0.y, a.x0.w, a.y0.w, desc0 + 128);
            wgmma_commit();
            wgmma_wait<1>();
            const uint32_t z1 = zero & mbar_test(sb + BAR_FULL, 0);
            t.y0 = lds128(ga[5]);
            n0 = tex128(idx_tex, tcoord);
            n1 = tex128(idx_tex, tcoord + 8 * PITCH4);
            tcoord += tstep;
            a.x1 = copy4(x1, z1); a.y1 = copy4(y1, z1);
            wgmma_fence();
            wgmma_rs(acc, a.x1.x, a.y1.x, a.x1.z, a.y1.z, desc0 + 64);
            __syncwarp();
            t.x1 = lds128(ga[6]);
            t.y1 = lds128(ga[7]);
            wgmma_rs(acc, a.x1.y, a.y1.y, a.x1.w, a.y1.w, desc0 + 192);
            wgmma_commit();
            wgmma_wait<1>();
            const uint32_t okv = mbar_test(sb + BAR_FULL + 8, 0);
            ok = okv != 0;
            const uint32_t z2 = zero & okv;
            A[1].x0 = copy4(t.x0, z2); A[1].y0 = copy4(t.y0, z2); A[1].x1 = copy4(t.x1, z2); A[1].y1 = copy4(t.y1, z2);
        }
        auto stage = [&](auto uc, int o) {
            constexpr int u = decltype(uc)::value;
            constexpr int slot = u % NST;
            const Frag& a = A[u & 1];
            if (u == UN - 3 && o + 1 == NOUT) mbar_wait(sb + BAR_EPI, 0);
            if (!ok) mbar_wait(sb + BAR_FULL + 8 * slot, u / NST);
            uint32_t g0, g1, g2, g3;
            if ((u & 1) == 0) {
                g0 = gaddr(i0.z); g1 = gaddr(i1.z); g2 = gaddr(i0.w); g3 = gaddr(i1.w);
            } else {
                i0 = n0; i1 = n1;
                g0 = gaddr(i0.x); g1 = gaddr(i1.x); g2 = gaddr(i0.y); g3 = gaddr(i1.y);
                if (u < UN - 3 || o + 1 < NOUT) {
                    n0 = tex128(idx_tex, tcoord);
                    n1 = tex128(idx_tex, tcoord + 8 * PITCH4);
                    tcoord += tstep;
                } else if (u == UN - 3) {
                    n0.x = kV; n1.x = kV + 1; n0.y = kV + 2; n1.y = kV + 3;
                }
            }
            const uint32_t d = desc0 + slot * (STAGE_BYTES >> 4);
            Frag t;
            wgmma_fence();
            t.x0 = lds128(g0);
            wgmma_rs(acc, a.x0.x, a.y0.x, a.x0.z, a.y0.z, d);
            __syncwarp();
            t.y0 = lds128(g1);
            wgmma_rs(acc, a.x0.y, a.y0.y, a.x0.w, a.y0.w, d + 128);
            __syncwarp();
            t.x1 = lds128(g2);
            wgmma_rs(acc, a.x1.x, a.y1.x, a.x1.z, a.y1.z, d + 64);
            __syncwarp();
            t.y1 = lds128(g3);
            wgmma_rs(acc, a.x1.y, a.y1.y, a.x1.w, a.y1.w, d + 192);
            wgmma_commit();
            wgmma_wait<1>();
            ok = mbar_test(sb + BAR_FULL + 8 * ((u + 1) % NST), ((u + 1) / NST) & 1) != 0;
            if ((u <= UN - NST || o + 1 < NOUT) && signaller) mbar_arrive(sb + BAR_EMPTY + 8 * ((u + NST - 1) % NST));
            Frag& an = A[(u + 1) & 1];
            an.x0 = copy4(t.x0, zero); an.y0 = copy4(t.y0, zero); an.x1 = copy4(t.x1, zero); an.y1 = copy4(t.y1, zero);
        };
#pragma unroll 1
        for (int o = 0;;) {
            stage(IC<1>{}, o); stage(IC<2>{}, o); stage(IC<3>{}, o);
            stage(IC<4>{}, o); stage(IC<5>{}, o); stage(IC<6>{}, o);
            stage(IC<7>{}, o); stage(IC<8>{}, o); stage(IC<9>{}, o);
            if (++o == NOUT) break;
            stage(IC<0>{}, o);
        }

        const uint32_t w2[16] = {A[0].x0.x, A[0].x0.y, A[0].x0.z, A[0].x0.w, A[0].y0.x, A[0].y0.y, A[0].y0.z, A[0].y0.w,
                                 A[0].x1.x, A[0].x1.y, A[0].x1.z, A[0].x1.w, A[0].y1.x, A[0].y1.y, A[0].y1.z, A[0].y1.w};
        float wide, b2f;
        asm volatile("ld.shared.v2.f32 {%0,%1}, [%2];" : "=f"(wide), "=f"(b2f) : "r"(wide_addr));
        wgmma_wait<0>();
#pragma unroll
        for (int i = 0; i < 64; i++) asm volatile("" : "+f"(acc[i])::"memory");
        float cc[4][4] = {};
#pragma unroll
        for (int s = 0; s < 8; s++) {
            uint32_t h[4];
#pragma unroll
            for (int i = 0; i < 4; i++)
                asm("cvt.rn.relu.bf16x2.f32 %0, %1, %2;" : "=r"(h[i]) : "f"(acc[8 * s + 2 * i + 1]), "f"(acc[8 * s + 2 * i]));
            float* c = cc[s & 3];
            asm volatile(
                "mma.sync.aligned.m16n8k16.row.col.f32.bf16.bf16.f32 {%0,%1,%2,%3}, {%4,%5,%6,%7}, {%8,%9}, {%0,%1,%2,%3};"
                : "+f"(c[0]), "+f"(c[1]), "+f"(c[2]), "+f"(c[3])
                : "r"(h[0]), "r"(h[1]), "r"(h[2]), "r"(h[3]), "r"(w2[2 * s]), "r"(w2[2 * s + 1]));
        }
        const bool hi = (tbase & 16) != 0;
        const float deep = hi ? (cc[0][2] + cc[1][2]) + (cc[2][2] + cc[3][2])
                              : (cc[0][0] + cc[1][0]) + (cc[2][0] + cc[3][0]);
        const float z = bf16r(wide + bf16r(bf16r(deep) + b2f));
        float e, p;
        asm("ex2.approx.ftz.f32 %0, %1;" : "=f"(e) : "f"(z * -1.4426950408889634f));
        asm("rcp.approx.ftz.f32 %0, %1;" : "=f"(p) : "f"(1.f + e));
        if (!(tbase & 32))
            asm volatile("st.global.b16 [%0], %1;" ::"l"(((uint64_t)out_hi << 32) | out_lo),
                         "h"(__bfloat16_as_ushort(__float2bfloat16_rn(p))) : "memory");
    }
}

typedef CUresult (*EncodeTiledFn)(CUtensorMap*, CUtensorMapDataType, cuuint32_t, void*, const cuuint64_t*,
                                  const cuuint64_t*, const cuuint32_t*, const cuuint32_t*, CUtensorMapInterleave,
                                  CUtensorMapSwizzle, CUtensorMapL2promotion, CUtensorMapFloatOOBfill);

}

extern "C" void kernel_launch(void* const* d_in, const int* in_sizes, int n_in, void* d_out, int out_size) {
    using namespace wd;
    (void)in_sizes; (void)n_in; (void)out_size;
    static EncodeTiledFn encode = nullptr;
    static cudaTextureObject_t idx_tex = 0;
    static const void* idx_tex_ptr = nullptr;
    if (!encode) {
        void* fn = nullptr;
        cudaDriverEntryPointQueryResult qr;
        cudaGetDriverEntryPoint("cuTensorMapEncodeTiled", &fn, cudaEnableDefault, &qr);
        encode = (EncodeTiledFn)fn;
        cudaFuncSetAttribute(wide_deep_kernel, cudaFuncAttributeMaxDynamicSharedMemorySize, SMEM_BYTES);
    }
    if (idx_tex_ptr != d_in[0]) {
        cudaResourceDesc rd = {};
        rd.resType = cudaResourceTypeLinear;
        rd.res.linear.devPtr = d_in[0];
        rd.res.linear.desc = cudaCreateChannelDesc(32, 32, 32, 32, cudaChannelFormatKindSigned);
        rd.res.linear.sizeInBytes = (size_t)kB * kF * 4;
        cudaTextureDesc td = {};
        td.readMode = cudaReadModeElementType;
        cudaCreateTextureObject(&idx_tex, &rd, &td, nullptr);
        idx_tex_ptr = d_in[0];
    }

    CUtensorMap tmW, tmI;
    {
        cuuint64_t dims[5] = {64, 2, 4 * (cuuint64_t)kF, 4, 2};
        cuuint64_t strides[4] = {256, 8 * 256, 2 * 256, 128};
        cuuint32_t box[5] = {64, 2, 4 * FPS, 4, 2};
        cuuint32_t es[5] = {1, 1, 1, 1, 1};
        encode(&tmW, CU_TENSOR_MAP_DATA_TYPE_BFLOAT16, 5, d_in[5], dims, strides, box, es,
               CU_TENSOR_MAP_INTERLEAVE_NONE, CU_TENSOR_MAP_SWIZZLE_128B, CU_TENSOR_MAP_L2_PROMOTION_L2_256B,
               CU_TENSOR_MAP_FLOAT_OOB_FILL_NONE);
    }
    {
        cuuint64_t dims[2] = {2 * (cuuint64_t)kF, (cuuint64_t)kB / 2};
        cuuint64_t strides[1] = {(cuuint64_t)kF * 8};
        cuuint32_t box[2] = {IDX_CH, BM};
        cuuint32_t es[2] = {1, 1};
        encode(&tmI, CU_TENSOR_MAP_DATA_TYPE_INT32, 2, d_in[0], dims, strides, box, es,
               CU_TENSOR_MAP_INTERLEAVE_NONE, CU_TENSOR_MAP_SWIZZLE_NONE, CU_TENSOR_MAP_L2_PROMOTION_NONE,
               CU_TENSOR_MAP_FLOAT_OOB_FILL_NONE);
    }
    wide_deep_kernel<<<NCTA, NTHREADS, SMEM_BYTES, cudaStreamPerThread>>>(
        (const int*)d_in[0], (const __nv_bfloat16*)d_in[1], (const __nv_bfloat16*)d_in[5], idx_tex, 0u,
        (const __nv_bfloat16*)d_in[6], (const __nv_bfloat16*)d_in[2], (const __nv_bfloat16*)d_in[3],
        (const __nv_bfloat16*)d_in[4], (const __nv_bfloat16*)d_in[7], (const __nv_bfloat16*)d_in[8],
        (__nv_bfloat16*)d_out, tmW, tmI);
}
```

```cpp
#include <cuda_runtime.h>
#include <cuda_bf16.h>
#include <cuda.h>
#include <stdint.h>

namespace wd {

constexpr int kB = 16384, kF = 100, kD = 32, kH = 128, kV = 1000, kNd = 13;
constexpr int BM = 128;
constexpr int NCTA = kB / BM;
constexpr int FPS = 2;
constexpr int STAGE_BYTES = FPS * kD * kH * 2;
constexpr int NST = 5;
constexpr int NSTEP = kF / FPS;
constexpr int UN = 2 * NST;
constexpr int NOUT = NSTEP / UN;
constexpr int IDX_F0 = 12;
constexpr int IDX_CH = 24;
constexpr int PITCH4 = kF / 2;
constexpr int TBL_BYTES = kV * kD * 2;
constexpr int X_BYTES = 2 * BM * kNd * 2;

constexpr int OFF_W = 0;
constexpr int OFF_TBL = OFF_W + NST * STAGE_BYTES;
constexpr int OFF_W2 = OFF_TBL + TBL_BYTES;
constexpr int OFF_B1 = OFF_W2 + 256;
constexpr int OFF_WIDE = OFF_B1 + 256;
constexpr int OFF_X = OFF_WIDE + 8 * BM;
constexpr int BAR_FULL = OFF_X + X_BYTES;
constexpr int BAR_EMPTY = BAR_FULL + 8 * NST;
constexpr int BAR_TBL = BAR_EMPTY + 8 * NST;
constexpr int BAR_B1 = BAR_TBL + 8;
constexpr int BAR_X = BAR_B1 + 8;
constexpr int BAR_EPI = BAR_X + 8;
constexpr int SMEM_BYTES = BAR_EPI + 8;
static_assert(SMEM_BYTES <= 232448, "smem");
static_assert(OFF_TBL % 64 == 0 && OFF_B1 % 16 == 0 && OFF_X % 16 == 0 && BAR_FULL % 8 == 0, "align");

constexpr int NTHREADS = 320;

__device__ __forceinline__ uint32_t smem_u32(const void* p) { return (uint32_t)__cvta_generic_to_shared(p); }
__device__ __forceinline__ void mbar_init(uint32_t bar, uint32_t cnt) {
    asm volatile("mbarrier.init.shared::cta.b64 [%0], %1;" ::"r"(bar), "r"(cnt) : "memory");
}
__device__ __forceinline__ void mbar_init_fence() {
    asm volatile("fence.mbarrier_init.release.cluster;" ::: "memory");
}
__device__ __forceinline__ void mbar_expect_tx(uint32_t bar, uint32_t bytes) {
    asm volatile("mbarrier.arrive.expect_tx.shared::cta.b64 _, [%0], %1;" ::"r"(bar), "r"(bytes) : "memory");
}
__device__ __forceinline__ void mbar_arrive(uint32_t bar) {
    asm volatile("mbarrier.arrive.shared::cta.b64 _, [%0];" ::"r"(bar) : "memory");
}
__device__ __forceinline__ uint32_t mbar_test(uint32_t bar, uint32_t parity) {
    uint32_t ok;
    asm volatile(
        "{\n\t.reg .pred p;\n\t"
        "mbarrier.test_wait.parity.shared::cta.b64 p, [%1], %2;\n\t"
        "selp.u32 %0, 1, 0, p;\n\t}"
        : "=r"(ok) : "r"(bar), "r"(parity) : "memory");
    return ok;
}
__device__ __forceinline__ void mbar_wait(uint32_t bar, uint32_t parity) {
    asm volatile(
        "{\n\t.reg .pred p;\n\t.reg .u32 n;\n\t"
        "mov.u32 n, 0;\n\t"
        "W_LOOP:\n\t"
        "mbarrier.try_wait.parity.shared::cta.b64 p, [%0], %1;\n\t"
        "@p bra W_DONE;\n\t"
        "add.u32 n, n, 1;\n\t"
        "setp.lt.u32 p, n, 4194304;\n\t"
        "@p bra W_LOOP;\n\t"
        "trap;\n\t"
        "W_DONE:\n\t}"
        ::"r"(bar), "r"(parity) : "memory");
}
__device__ __forceinline__ void bulk_load(uint32_t dst, const void* src, uint32_t bytes, uint32_t bar) {
    mbar_expect_tx(bar, bytes);
    asm volatile("cp.async.bulk.shared::cluster.global.mbarrier::complete_tx::bytes [%0], [%1], %2, [%3];"
                 ::"r"(dst), "l"(src), "r"(bytes), "r"(bar) : "memory");
}
__device__ __forceinline__ void prefetch_line(const void* p) {
    asm volatile("prefetch.global.L2 [%0];" ::"l"(p) : "memory");
}
__device__ __forceinline__ uint4 lds128(uint32_t addr) {
    uint4 v;
    asm volatile("ld.shared.v4.u32 {%0,%1,%2,%3}, [%4];" : "=r"(v.x), "=r"(v.y), "=r"(v.z), "=r"(v.w) : "r"(addr));
    return v;
}
__device__ __forceinline__ uint4 ldg128(const uint4* p) {
    uint4 v;
    asm volatile("ld.global.v4.u32 {%0,%1,%2,%3}, [%4];"
                 : "=r"(v.x), "=r"(v.y), "=r"(v.z), "=r"(v.w) : "l"(p) : "memory");
    return v;
}
__device__ __forceinline__ uint4 tex128(cudaTextureObject_t t, int i) {
    uint4 v;
    asm volatile("tex.1d.v4.s32.s32 {%0,%1,%2,%3}, [%4, {%5}];"
                 : "=r"(v.x), "=r"(v.y), "=r"(v.z), "=r"(v.w) : "l"(t), "r"(i));
    return v;
}
__device__ __forceinline__ void cta_sync() { asm volatile("barrier.sync 1, %0;" ::"n"(NTHREADS) : "memory"); }
__device__ __forceinline__ bool elect() {
    uint32_t p;
    asm volatile("{\n\t.reg .pred P;\n\telect.sync _|P, 0xffffffff;\n\tselp.u32 %0, 1, 0, P;\n\t}" : "=r"(p));
    return p != 0;
}
__device__ __forceinline__ uint4 copy4(uint4 t, uint32_t z) {
    uint4 r;
    asm volatile("xor.b32 %0, %1, %2;" : "=r"(r.x) : "r"(t.x), "r"(z));
    asm volatile("xor.b32 %0, %1, %2;" : "=r"(r.y) : "r"(t.y), "r"(z));
    asm volatile("xor.b32 %0, %1, %2;" : "=r"(r.z) : "r"(t.z), "r"(z));
    asm volatile("xor.b32 %0, %1, %2;" : "=r"(r.w) : "r"(t.w), "r"(z));
    return r;
}
__device__ __forceinline__ uint32_t pin(uint32_t v, int lane) { return __shfl_sync(0xffffffffu, v, lane); }

__device__ __forceinline__ void wgmma_fence() { asm volatile("wgmma.fence.sync.aligned;" ::: "memory"); }
__device__ __forceinline__ void wgmma_commit() { asm volatile("wgmma.commit_group.sync.aligned;" ::: "memory"); }
template <int N>
__device__ __forceinline__ void wgmma_wait() { asm volatile("wgmma.wait_group.sync.aligned %0;" ::"n"(N) : "memory"); }

template <int ACC = 1>
__device__ __forceinline__ void wgmma_rs(float (&d)[64], uint32_t a0, uint32_t a1, uint32_t a2, uint32_t a3,
                                         uint32_t desc_lo) {
    asm volatile(
        "{\n\t.reg .b64 dsc;\n\t"
        "mov.b64 dsc, {%68, %69};\n\t"
        "wgmma.mma_async.sync.aligned.m64n128k16.f32.bf16.bf16 "
        "{%0,%1,%2,%3,%4,%5,%6,%7,%8,%9,%10,%11,%12,%13,%14,%15,"
        "%16,%17,%18,%19,%20,%21,%22,%23,%24,%25,%26,%27,%28,%29,%30,%31,"
        "%32,%33,%34,%35,%36,%37,%38,%39,%40,%41,%42,%43,%44,%45,%46,%47,"
        "%48,%49,%50,%51,%52,%53,%54,%55,%56,%57,%58,%59,%60,%61,%62,%63},"
        "{%64,%65,%66,%67}, dsc, %70, 1, 1, 1;\n\t}"
        : "+f"(d[0]), "+f"(d[1]), "+f"(d[2]), "+f"(d[3]), "+f"(d[4]), "+f"(d[5]), "+f"(d[6]), "+f"(d[7]),
          "+f"(d[8]), "+f"(d[9]), "+f"(d[10]), "+f"(d[11]), "+f"(d[12]), "+f"(d[13]), "+f"(d[14]), "+f"(d[15]),
          "+f"(d[16]), "+f"(d[17]), "+f"(d[18]), "+f"(d[19]), "+f"(d[20]), "+f"(d[21]), "+f"(d[22]), "+f"(d[23]),
          "+f"(d[24]), "+f"(d[25]), "+f"(d[26]), "+f"(d[27]), "+f"(d[28]), "+f"(d[29]), "+f"(d[30]), "+f"(d[31]),
          "+f"(d[32]), "+f"(d[33]), "+f"(d[34]), "+f"(d[35]), "+f"(d[36]), "+f"(d[37]), "+f"(d[38]), "+f"(d[39]),
          "+f"(d[40]), "+f"(d[41]), "+f"(d[42]), "+f"(d[43]), "+f"(d[44]), "+f"(d[45]), "+f"(d[46]), "+f"(d[47]),
          "+f"(d[48]), "+f"(d[49]), "+f"(d[50]), "+f"(d[51]), "+f"(d[52]), "+f"(d[53]), "+f"(d[54]), "+f"(d[55]),
          "+f"(d[56]), "+f"(d[57]), "+f"(d[58]), "+f"(d[59]), "+f"(d[60]), "+f"(d[61]), "+f"(d[62]), "+f"(d[63])
        : "r"(a0), "r"(a1), "r"(a2), "r"(a3), "r"(desc_lo), "n"(0x40000000 | (4096 >> 4)), "n"(ACC));
}

__device__ __forceinline__ float bf16r(float x) {
    uint32_t p;
    asm("cvt.rn.bf16x2.f32 %0, %1, %2;" : "=r"(p) : "f"(x), "f"(0.f));
    return __uint_as_float(p);
}

template <int N> struct IC { static constexpr int value = N; };
struct Frag { uint4 x0, y0, x1, y1; };

__global__ void __launch_bounds__(NTHREADS, 1)
wide_deep_kernel(const int* __restrict__ idx, const __nv_bfloat16* __restrict__ table,
                 const __nv_bfloat16* __restrict__ W1, cudaTextureObject_t idx_tex, uint32_t zero,
                 const __nv_bfloat16* __restrict__ b1, const __nv_bfloat16* __restrict__ x_wide,
                 const __nv_bfloat16* __restrict__ w_wide, const __nv_bfloat16* __restrict__ b_wide,
                 const __nv_bfloat16* __restrict__ W2, const __nv_bfloat16* __restrict__ b2,
                 __nv_bfloat16* __restrict__ out,
                 const __grid_constant__ CUtensorMap tmW, const __grid_constant__ CUtensorMap tmI) {
    extern __shared__ __align__(1024) uint8_t smem_raw[];
    const uint32_t sb = smem_u32(smem_raw);
    const int tid = threadIdx.x;
    const int lane = tid & 31;

    if (tid >= 288) {
        const int c = blockIdx.x & 31;
        if (lane < 16) prefetch_line((const uint8_t*)table + min(c * 16 + lane, 499) * 128);
        if (lane < 8) prefetch_line((const uint8_t*)W1 + (c * 4 + (lane >> 1) + (lane & 1) * ((NSTEP - 2) * 128)) * 128);
    }
    const int warp = __shfl_sync(0xffffffffu, tid >> 5, 0);

    const int asc = blockIdx.x & 1;
    const int pair = blockIdx.x >> 1;
    const int prow0 = pair * BM;

    if (warp == 8) {
        auto load_w = [&](int step, int slot) {
            const int fp = asc ? step : (NSTEP - 2) - step + 2 * (step & 1);
            const uint32_t bar = sb + BAR_FULL + 8 * slot;
            mbar_expect_tx(bar, STAGE_BYTES);
            asm volatile(
                "cp.async.bulk.tensor.5d.shared::cluster.global.mbarrier::complete_tx::bytes "
                "[%0], [%1, {0, 0, %3, 0, 0}], [%2];"
                ::"r"(sb + OFF_W + slot * STAGE_BYTES), "l"(&tmW), "r"(bar), "r"(fp * (4 * FPS)) : "memory");
        };
        auto prefetch_idx = [&](int c) {
            const int f = IDX_F0 + c * IDX_CH;
            asm volatile("cp.async.bulk.prefetch.tensor.2d.L2.global [%0, {%1, %2}];"
                         ::"l"(&tmI), "r"(asc ? kF + f : kF - f - IDX_CH), "r"(prow0) : "memory");
        };
        if (elect()) {
            asm volatile("prefetch.tensormap [%0];" ::"l"(&tmW) : "memory");
            mbar_init(sb + BAR_TBL, 1);
            mbar_init(sb + BAR_FULL, 1);
            mbar_init(sb + BAR_B1, 1);
            mbar_init_fence();
            bulk_load(sb + OFF_B1, b1, 256, sb + BAR_B1);
            load_w(0, 0);
            bulk_load(sb + OFF_TBL, table, TBL_BYTES, sb + BAR_TBL);
            asm volatile("prefetch.tensormap [%0];" ::"l"(&tmI) : "memory");
            for (int s = 1; s < NST; s++) mbar_init(sb + BAR_FULL + 8 * s, 1);
            for (int s = 0; s < NST; s++) mbar_init(sb + BAR_EMPTY + 8 * s, 2);
            mbar_init(sb + BAR_X, 1);
            mbar_init(sb + BAR_EPI, 32);
            mbar_init_fence();
        }
        cta_sync();
        if (elect()) {
            mbar_wait(sb + BAR_FULL, 0);
            load_w(1, 1);
            mbar_wait(sb + BAR_TBL, 0);
            for (int s = 2; s < NST; s++) load_w(s, s);
            prefetch_idx(0);
            constexpr int MID = (NSTEP - 2 * NST) * STAGE_BYTES / NCTA;
            asm volatile("cp.async.bulk.prefetch.L2.global [%0], %1;"
                         ::"l"((const uint8_t*)W1 + NST * STAGE_BYTES + blockIdx.x * MID), "n"(MID) : "memory");
            bulk_load(sb + OFF_X, (const uint8_t*)x_wide + pair * X_BYTES, X_BYTES, sb + BAR_X);
            int slot = 0, nextc = 1;
            uint32_t ph = 0;
#pragma unroll 1
            for (int step = NST; step < NSTEP; step++) {
                mbar_wait(sb + BAR_EMPTY + 8 * slot, ph);
                load_w(step, slot);
                if (++slot == NST) { slot = 0; ph ^= 1; }
                if (IDX_F0 + nextc * IDX_CH < kF && step == NST + nextc * 6) prefetch_idx(nextc++);
            }
        }
    } else if (warp == 9) {
        if (lane < 2 * NST) {
            const int i = blockIdx.x * NST + (lane >> 1);
            prefetch_line((const uint8_t*)W1 + ((lane & 1) ? NSTEP * 128 - 1 - i : i) * 128);
        }
        {
            const int tc = (prow0 + lane) * PITCH4 + (kF / 4 - 1) + (asc ? 2 : -1);
            uint4 v[4];
#pragma unroll
            for (int r = 0; r < 4; r++) v[r] = tex128(idx_tex, tc + 32 * r * PITCH4);
            cta_sync();
            if (((v[0].x | v[1].x | v[2].x | v[3].x) & zero) != 0) __trap();
        }
        mbar_wait(sb + BAR_X, 0);
#pragma unroll
        for (int h = 0; h < 2; h++) {
            ((uint32_t*)(smem_raw + OFF_W2))[32 * h + (lane & 4) * 4 + (lane & 3) * 4 + (lane >> 3)] =
                __ldg((const uint32_t*)W2 + lane + 32 * h);
        }
        const float wl = (lane >= asc && lane < kNd + asc) ? __bfloat162float(w_wide[lane - asc]) : 0.f;
        const float bw = __bfloat162float(b_wide[0]);
        const float b2v = __bfloat162float(b2[0]);
        float wt[14];
#pragma unroll
        for (int j = 0; j < 14; j++) wt[j] = __shfl_sync(0xffffffffu, wl, j);
#pragma unroll
        for (int r = 0; r < 4; r++) {
            const uint32_t* x = (const uint32_t*)(smem_raw + OFF_X) + (lane + 32 * r) * kNd + 6 * asc;
            float s = 0.f;
#pragma unroll
            for (int j = 0; j < 7; j++) {
                uint32_t v = x[j];
                if (j == 0 && asc) v &= 0xffff0000u;
                if (j == 6 && !asc) v &= 0x0000ffffu;
                s = fmaf(__uint_as_float(v << 16), wt[2 * j], s);
                s = fmaf(__uint_as_float(v & 0xffff0000u), wt[2 * j + 1], s);
            }
            ((float2*)(smem_raw + OFF_WIDE))[lane + 32 * r] = make_float2(bf16r(bf16r(s) + bw), b2v);
        }
        mbar_arrive(sb + BAR_EPI);
    } else {
        const int q = lane & 3;
        const int r0 = warp * 16 + (lane >> 2);
        const int tstep = asc ? 1 : -1;
        int tcoord = (prow0 + r0) * PITCH4 + (kF / 4 - 1) + asc;
        const uint4 f0 = ldg128((const uint4*)idx + tcoord), f1 = ldg128((const uint4*)idx + tcoord + 8 * PITCH4);
        tcoord += tstep;
        cta_sync();

        float acc[64];

        const uint64_t outp = (uint64_t)(out + 2 * (prow0 + r0 + 8 * (q & 1)) + asc);
        const uint32_t out_lo = pin((uint32_t)outp, lane), out_hi = pin((uint32_t)(outp >> 32), lane);
        const uint32_t wide_addr = pin(sb + OFF_WIDE + (r0 + 8 * (q & 1)) * 8, lane);
        const uint32_t tbase = pin(sb + OFF_TBL + q * 16, lane);
        auto gaddr = [&](uint32_t v) -> uint32_t { return tbase + v * 64; };
        const bool signaller = (tid & 127) == 0;
        const uint32_t desc0 = (((sb + OFF_W) & 0x3FFFF) >> 4) | ((8192 >> 4) << 16);

        uint32_t b1p[16];
        mbar_wait(sb + BAR_B1, 0);
#pragma unroll
        for (int n = 0; n < 16; n++)
            asm volatile("ld.shared.u32 %0, [%1];" : "=r"(b1p[n]) : "r"(sb + OFF_B1 + 16 * n + 4 * q) : "memory");
        mbar_wait(sb + BAR_FULL, 0);
        const uint32_t ga[8] = {gaddr(f0.x), gaddr(f1.x), gaddr(f0.y), gaddr(f1.y),
                                gaddr(f0.z), gaddr(f1.z), gaddr(f0.w), gaddr(f1.w)};
        mbar_wait(sb + BAR_TBL, 0);

        Frag A[2];
        uint4 i0 = f0, i1 = f1, n0, n1;
        bool ok;
        {
            Frag t;
            Frag& a = A[0];
            const uint4 x0 = lds128(ga[0]), y0 = lds128(ga[1]);
            __syncwarp();
            const uint4 x1 = lds128(ga[2]), y1 = lds128(ga[3]);
            __syncwarp();
            a.x0 = copy4(x0, zero); a.y0 = copy4(y0, zero);
            wgmma_fence();
            wgmma_rs<0>(acc, a.x0.x, a.y0.x, a.x0.z, a.y0.z, desc0);
            __syncwarp();
            t.x0 = lds128(ga[4]);
            wgmma_rs(acc, a.x0.y, a.y0.y, a.x0.w, a.y0.w, desc0 + 128);
            wgmma_commit();
            wgmma_wait<1>();
            const uint32_t z1 = zero & mbar_test(sb + BAR_FULL, 0);
            t.y0 = lds128(ga[5]);
            n0 = tex128(idx_tex, tcoord);
            n1 = tex128(idx_tex, tcoord + 8 * PITCH4);
            tcoord += tstep;
            a.x1 = copy4(x1, z1); a.y1 = copy4(y1, z1);
            wgmma_fence();
            wgmma_rs(acc, a.x1.x, a.y1.x, a.x1.z, a.y1.z, desc0 + 64);
            __syncwarp();
            t.x1 = lds128(ga[6]);
            t.y1 = lds128(ga[7]);
            wgmma_rs(acc, a.x1.y, a.y1.y, a.x1.w, a.y1.w, desc0 + 192);
            wgmma_commit();
            wgmma_wait<1>();
            const uint32_t okv = mbar_test(sb + BAR_FULL + 8, 0);
            ok = okv != 0;
            const uint32_t z2 = zero & okv;
            A[1].x0 = copy4(t.x0, z2); A[1].y0 = copy4(t.y0, z2); A[1].x1 = copy4(t.x1, z2); A[1].y1 = copy4(t.y1, z2);
        }
        auto stage = [&](auto uc, int o) {
            constexpr int u = decltype(uc)::value;
            constexpr int slot = u % NST;
            const Frag& a = A[u & 1];
            if (u == UN - 3 && o + 1 == NOUT) mbar_wait(sb + BAR_EPI, 0);
            if (!ok) mbar_wait(sb + BAR_FULL + 8 * slot, u / NST);
            uint32_t g0, g1, g2, g3;
            if ((u & 1) == 0) {
                g0 = gaddr(i0.z); g1 = gaddr(i1.z); g2 = gaddr(i0.w); g3 = gaddr(i1.w);
            } else {
                i0 = n0; i1 = n1;
                g0 = gaddr(i0.x); g1 = gaddr(i1.x); g2 = gaddr(i0.y); g3 = gaddr(i1.y);
                if (u < UN - 3 || o + 1 < NOUT) {
                    n0 = tex128(idx_tex, tcoord);
                    n1 = tex128(idx_tex, tcoord + 8 * PITCH4);
                    tcoord += tstep;
                } else if (u == UN - 3) {
                    n0.x = kV; n1.x = kV + 1; n0.y = kV + 2; n1.y = kV + 3;
                }
            }
            const uint32_t d = desc0 + slot * (STAGE_BYTES >> 4);
            Frag t;
            wgmma_fence();
            t.x0 = lds128(g0);
            wgmma_rs(acc, a.x0.x, a.y0.x, a.x0.z, a.y0.z, d);
            __syncwarp();
            t.y0 = lds128(g1);
            wgmma_rs(acc, a.x0.y, a.y0.y, a.x0.w, a.y0.w, d + 128);
            __syncwarp();
            t.x1 = lds128(g2);
            wgmma_rs(acc, a.x1.x, a.y1.x, a.x1.z, a.y1.z, d + 64);
            __syncwarp();
            t.y1 = lds128(g3);
            wgmma_rs(acc, a.x1.y, a.y1.y, a.x1.w, a.y1.w, d + 192);
            wgmma_commit();
            wgmma_wait<1>();
            ok = mbar_test(sb + BAR_FULL + 8 * ((u + 1) % NST), ((u + 1) / NST) & 1) != 0;
            if ((u <= UN - NST || o + 1 < NOUT) && signaller) mbar_arrive(sb + BAR_EMPTY + 8 * ((u + NST - 1) % NST));
            Frag& an = A[(u + 1) & 1];
            an.x0 = copy4(t.x0, zero); an.y0 = copy4(t.y0, zero); an.x1 = copy4(t.x1, zero); an.y1 = copy4(t.y1, zero);
        };
#pragma unroll 1
        for (int o = 0;;) {
            stage(IC<1>{}, o); stage(IC<2>{}, o); stage(IC<3>{}, o);
            stage(IC<4>{}, o); stage(IC<5>{}, o); stage(IC<6>{}, o);
            stage(IC<7>{}, o); stage(IC<8>{}, o); stage(IC<9>{}, o);
            if (++o == NOUT) break;
            stage(IC<0>{}, o);
        }

        const uint32_t w2[16] = {A[0].x0.x, A[0].y0.x, A[0].x0.y, A[0].y0.y, A[0].x0.z, A[0].y0.z, A[0].x0.w, A[0].y0.w,
                                 A[0].x1.x, A[0].y1.x, A[0].x1.y, A[0].y1.y, A[0].x1.z, A[0].y1.z, A[0].x1.w, A[0].y1.w};
        float wide, b2f;
        asm volatile("ld.shared.v2.f32 {%0,%1}, [%2];" : "=f"(wide), "=f"(b2f) : "r"(wide_addr));
        wgmma_wait<0>();
#pragma unroll
        for (int i = 0; i < 64; i++) asm volatile("" : "+f"(acc[i])::"memory");
        float cc[4][4] = {};
#pragma unroll
        for (int s = 0; s < 8; s++) {
            uint32_t h[4];
#pragma unroll
            for (int i = 0; i < 4; i++) {
                uint32_t pk;
                asm("cvt.rn.bf16x2.f32 %0, %1, %2;" : "=r"(pk) : "f"(acc[8 * s + 2 * i + 1]), "f"(acc[8 * s + 2 * i]));
                asm("fma.rn.relu.bf16x2 %0, %1, %2, %3;" : "=r"(h[i]) : "r"(pk), "r"(0x3f803f80u), "r"(b1p[2 * s + (i >> 1)]));
            }
            float* c = cc[s & 3];
            asm volatile(
                "mma.sync.aligned.m16n8k16.row.col.f32.bf16.bf16.f32 {%0,%1,%2,%3}, {%4,%5,%6,%7}, {%8,%9}, {%0,%1,%2,%3};"
                : "+f"(c[0]), "+f"(c[1]), "+f"(c[2]), "+f"(c[3])
                : "r"(h[0]), "r"(h[1]), "r"(h[2]), "r"(h[3]), "r"(w2[2 * s]), "r"(w2[2 * s + 1]));
        }
        const bool hi = (tbase & 16) != 0;
        const float deep = hi ? (cc[0][2] + cc[1][2]) + (cc[2][2] + cc[3][2])
                              : (cc[0][0] + cc[1][0]) + (cc[2][0] + cc[3][0]);
        const float z = bf16r(wide + bf16r(bf16r(deep) + b2f));
        float e, p;
        asm("ex2.approx.ftz.f32 %0, %1;" : "=f"(e) : "f"(z * -1.4426950408889634f));
        asm("rcp.approx.ftz.f32 %0, %1;" : "=f"(p) : "f"(1.f + e));
        if (!(tbase & 32))
            asm volatile("st.global.b16 [%0], %1;" ::"l"(((uint64_t)out_hi << 32) | out_lo),
                         "h"(__bfloat16_as_ushort(__float2bfloat16_rn(p))) : "memory");
    }
}

typedef CUresult (*EncodeTiledFn)(CUtensorMap*, CUtensorMapDataType, cuuint32_t, void*, const cuuint64_t*,
                                  const cuuint64_t*, const cuuint32_t*, const cuuint32_t*, CUtensorMapInterleave,
                                  CUtensorMapSwizzle, CUtensorMapL2promotion, CUtensorMapFloatOOBfill);

}

extern "C" void kernel_launch(void* const* d_in, const int* in_sizes, int n_in, void* d_out, int out_size) {
    using namespace wd;
    (void)in_sizes; (void)n_in; (void)out_size;
    static EncodeTiledFn encode = nullptr;
    static cudaTextureObject_t idx_tex = 0;
    static const void* idx_tex_ptr = nullptr;
    if (!encode) {
        void* fn = nullptr;
        cudaDriverEntryPointQueryResult qr;
        cudaGetDriverEntryPoint("cuTensorMapEncodeTiled", &fn, cudaEnableDefault, &qr);
        encode = (EncodeTiledFn)fn;
        cudaFuncSetAttribute(wide_deep_kernel, cudaFuncAttributeMaxDynamicSharedMemorySize, SMEM_BYTES);
    }
    if (idx_tex_ptr != d_in[0]) {
        cudaResourceDesc rd = {};
        rd.resType = cudaResourceTypeLinear;
        rd.res.linear.devPtr = d_in[0];
        rd.res.linear.desc = cudaCreateChannelDesc(32, 32, 32, 32, cudaChannelFormatKindSigned);
        rd.res.linear.sizeInBytes = (size_t)kB * kF * 4;
        cudaTextureDesc td = {};
        td.readMode = cudaReadModeElementType;
        cudaCreateTextureObject(&idx_tex, &rd, &td, nullptr);
        idx_tex_ptr = d_in[0];
    }

    CUtensorMap tmW, tmI;
    {
        cuuint64_t dims[5] = {64, 2, 4 * (cuuint64_t)kF, 4, 2};
        cuuint64_t strides[4] = {256, 8 * 256, 2 * 256, 128};
        cuuint32_t box[5] = {64, 2, 4 * FPS, 4, 2};
        cuuint32_t es[5] = {1, 1, 1, 1, 1};
        encode(&tmW, CU_TENSOR_MAP_DATA_TYPE_BFLOAT16, 5, d_in[5], dims, strides, box, es,
               CU_TENSOR_MAP_INTERLEAVE_NONE, CU_TENSOR_MAP_SWIZZLE_128B, CU_TENSOR_MAP_L2_PROMOTION_L2_256B,
               CU_TENSOR_MAP_FLOAT_OOB_FILL_NONE);
    }
    {
        cuuint64_t dims[2] = {2 * (cuuint64_t)kF, (cuuint64_t)kB / 2};
        cuuint64_t strides[1] = {(cuuint64_t)kF * 8};
        cuuint32_t box[2] = {IDX_CH, BM};
        cuuint32_t es[2] = {1, 1};
        encode(&tmI, CU_TENSOR_MAP_DATA_TYPE_INT32, 2, d_in[0], dims, strides, box, es,
               CU_TENSOR_MAP_INTERLEAVE_NONE, CU_TENSOR_MAP_SWIZZLE_NONE, CU_TENSOR_MAP_L2_PROMOTION_NONE,
               CU_TENSOR_MAP_FLOAT_OOB_FILL_NONE);
    }
    wide_deep_kernel<<<NCTA, NTHREADS, SMEM_BYTES, cudaStreamPerThread>>>(
        (const int*)d_in[0], (const __nv_bfloat16*)d_in[1], (const __nv_bfloat16*)d_in[5], idx_tex, 0u,
        (const __nv_bfloat16*)d_in[6], (const __nv_bfloat16*)d_in[2], (const __nv_bfloat16*)d_in[3],
        (const __nv_bfloat16*)d_in[4], (const __nv_bfloat16*)d_in[7], (const __nv_bfloat16*)d_in[8],
        (__nv_bfloat16*)d_out, tmW, tmI);
}
```
